```python
import torch

def _softmax(x, axis=-1):
    return torch.softmax(x, dim=axis)
def _gelu(x):
    return torch.nn.functional.gelu(x, approximate="tanh")
def _silu(x):
    return torch.nn.functional.silu(x)
def _sigmoid(x):
    return torch.sigmoid(x)
def _layernorm(x, axis=-1, eps=1e-5):
    m = x.mean(dim=axis, keepdim=True)
    v = x.var(dim=axis, keepdim=True, unbiased=False)
    return (x - m) / torch.sqrt(v + eps)
def _scatter_add(tgt, idx, src, axis=0):
    return tgt.clone().index_add_(axis, idx, src)
def _segment_sum(src, seg, n):
    out = torch.zeros((n,) + src.shape[1:], dtype=src.dtype)
    return out.index_add_(0, seg, src)
def _pad(x, pw):
    flat = tuple(v for pair in reversed(pw) for v in pair)
    return torch.nn.functional.pad(x, flat)

kernel_name = 'standalone__weight_only_int_gptq__prompt'

def setup_inputs():

    _w = (lambda a: (lambda t: t.to(torch.bfloat16) if t.is_floating_point() else t)(torch.as_tensor(a)))
    B, S, D, F = 1, 2048, 576, 4608
    bits = max(2, min(4, 2))
    pf = 32 // bits
    G = 64 if 64 > 0 else D
    G = max(pf, (G // pf) * pf)
    D = max(G, (D // G) * G)
    ng = D // G
    qmax = 1 << bits
    qw = torch.randint(0, qmax, (D, F)).to(torch.int64)
    packed = torch.zeros((D // pf, F), dtype=torch.int64)
    for i in range(pf):
        packed |= (qw[i::pf] << (i * bits))
    packed = packed.to(torch.int32)
    return {
        "x": _w((lambda *s: torch.randn(*s, dtype=torch.bfloat16) * 0.05)(B, S, D)),
        "qw_packed": _w(packed),
        "scales": _w(torch.abs((lambda *s: torch.randn(*s, dtype=torch.bfloat16) * 0.05)(ng, F)).to(float) * 0.1 + 0.01),
        "zeros": _w(torch.randint(0, qmax, (ng, F)).to(float)),
        "bits": _w((lambda _x: torch.as_tensor(_x, dtype=torch.int32))(bits)),
    }

def reference(x, qw_packed, scales, zeros, bits):
    b = int(bits)
    pf = 32 // b
    mask = (1 << b) - 1
    P, F = qw_packed.shape
    D = P * pf
    ng = scales.shape[0]
    G = D // ng
    shifts = (lambda x, dt: x.to(dt))(torch.arange(pf) * b, qw_packed.dtype)
    qw = ((qw_packed[:, None, :] >> shifts[None, :, None]) & mask).reshape(D, F)
    s = (lambda x, n, axis: torch.repeat_interleave(x, n, dim=axis))(scales, G, axis=0)
    z = (lambda x, n, axis: torch.repeat_interleave(x, n, dim=axis))(zeros, G, axis=0)
    w = ((lambda x, dt: x.to(dt))(qw, x.dtype) - z) * s
    return torch.einsum("bsd,df->bsf", x, w)
```

```cpp
#include <cuda_runtime.h>
#include <cuda_bf16.h>
#include <cuda.h>
#include <stdint.h>

namespace {

constexpr int S_TOK = 2048, D_K = 576, F_N = 4608, NGRP = 9;
constexpr int BT = 128;
constexpr int NWG = 3;
constexpr int GRID = 132;
constexpr int WG96 = 1;
constexpr int XBLK = BT * 128;
constexpr int WRAW = 12 * 256;
constexpr int WSLOT = WRAW + 3 * 512;
constexpr int SM_X = 0;
constexpr int SM_O = NGRP * XBLK;
constexpr int SM_W = SM_O + NWG * 16384;
constexpr int SM_BAR = SM_W + NWG * 2 * WSLOT;
constexpr int SM_FULL = SM_BAR + 80;
constexpr int SM_EMPTY = SM_FULL + NWG * 16;
constexpr int SM_STAGED = SM_EMPTY + NWG * 8;
constexpr int SM_CONST = SM_STAGED + NWG * 8;
constexpr int SM_TOTAL = SM_CONST + 32;

__device__ __align__(128) uint8_t g_prep[72 * 3 * WSLOT];
__device__ uint32_t g_ready[8 * 32];


__device__ __forceinline__ void mbar_init(uint32_t bar, uint32_t cnt) {
    asm volatile("mbarrier.init.shared::cta.b64 [%0], %1;" ::"r"(bar), "r"(cnt));
}
__device__ __forceinline__ void mbar_init_fence() { asm volatile("fence.mbarrier_init.release.cluster;" ::: "memory"); }
__device__ __forceinline__ void mbar_expect_tx(uint32_t bar, uint32_t bytes) {
    asm volatile("mbarrier.arrive.expect_tx.shared::cta.b64 _, [%0], %1;" ::"r"(bar), "r"(bytes) : "memory");
}
__device__ __forceinline__ void mbar_arrive(uint32_t bar) {
    asm volatile("mbarrier.arrive.shared::cta.b64 _, [%0];" ::"r"(bar) : "memory");
}
__device__ __forceinline__ void mbar_wait(uint32_t bar, uint32_t parity) {
    asm volatile("{\n.reg .pred p;\n.reg .u32 c;\n"
                 "mbarrier.try_wait.parity.shared::cta.b64 p, [%0], %1;\n"
                 "@p bra LAB_DONE;\n"
                 "mov.u32 c, 0;\n"
                 "LAB_WAIT:\n"
                 "mbarrier.try_wait.parity.shared::cta.b64 p, [%0], %1;\n"
                 "@p bra LAB_DONE;\n"
                 "add.u32 c, c, 1;\n"
                 "setp.lt.u32 p, c, 0x400000;\n"
                 "@p bra LAB_WAIT;\n"
                 "trap;\n"
                 "LAB_DONE:\n}\n" ::"r"(bar), "r"(parity) : "memory");
}
__device__ __forceinline__ void tma_load_2d(uint32_t dst, const CUtensorMap* m, int c0, int c1, uint32_t bar) {
    asm volatile("cp.async.bulk.tensor.2d.shared::cluster.global.mbarrier::complete_tx::bytes [%0], [%1, {%3, %4}], [%2];"
                 ::"r"(dst), "l"(m), "r"(bar), "r"(c0), "r"(c1) : "memory");
}
__device__ __forceinline__ void tma_load_3d(uint32_t dst, const CUtensorMap* m, int c0, int c1, int c2, uint32_t bar) {
    asm volatile("cp.async.bulk.tensor.3d.shared::cluster.global.mbarrier::complete_tx::bytes [%0], [%1, {%3, %4, %5}], [%2];"
                 ::"r"(dst), "l"(m), "r"(bar), "r"(c0), "r"(c1), "r"(c2) : "memory");
}
__device__ __forceinline__ void tma_store_2d(const CUtensorMap* m, int c0, int c1, uint32_t src) {
    asm volatile("cp.async.bulk.tensor.2d.global.shared::cta.bulk_group [%0, {%2, %3}], [%1];"
                 ::"l"(m), "r"(src), "r"(c0), "r"(c1) : "memory");
}
__device__ __forceinline__ void bulk_load(uint32_t dst, const void* src, uint32_t bytes, uint32_t bar) {
    asm volatile("cp.async.bulk.shared::cluster.global.mbarrier::complete_tx::bytes [%0], [%1], %2, [%3];"
                 ::"r"(dst), "l"(src), "r"(bytes), "r"(bar) : "memory");
}
__device__ __forceinline__ void bulk_commit() { asm volatile("cp.async.bulk.commit_group;" ::: "memory"); }
__device__ __forceinline__ void bulk_wait_read() { asm volatile("cp.async.bulk.wait_group.read 0;" ::: "memory"); }
__device__ __forceinline__ void proxy_fence_shared() { asm volatile("fence.proxy.async.shared::cta;" ::: "memory"); }
__device__ __forceinline__ bool elect_one() {
    uint32_t p;
    asm volatile("{\n.reg .pred q;\nelect.sync _|q, 0xffffffff;\nselp.b32 %0, 1, 0, q;\n}\n" : "=r"(p));
    return p != 0;
}
__device__ __forceinline__ void wg_fence() { asm volatile("wgmma.fence.sync.aligned;" ::: "memory"); }
__device__ __forceinline__ void wg_commit() { asm volatile("wgmma.commit_group.sync.aligned;" ::: "memory"); }
template <int N> __device__ __forceinline__ void wg_wait() { asm volatile("wgmma.wait_group.sync.aligned %0;" ::"n"(N) : "memory"); }
__device__ __forceinline__ void bar_sync(int id, int n) { asm volatile("bar.sync %0, %1;" ::"r"(id), "r"(n) : "memory"); }
__device__ __forceinline__ void bar_arrive(int id, int n) { asm volatile("bar.arrive %0, %1;" ::"r"(id), "r"(n) : "memory"); }
__device__ __forceinline__ uint32_t ldg32(const void* p) {
    uint32_t v;
    asm volatile("ld.global.nc.b32 %0, [%1];" : "=r"(v) : "l"(p));
    return v;
}
__device__ __forceinline__ void ldg64(const void* p, uint32_t& a, uint32_t& b) {
    asm volatile("ld.global.nc.v2.b32 {%0, %1}, [%2];" : "=r"(a), "=r"(b) : "l"(p));
}
__device__ __forceinline__ void stg128(void* p, uint32_t a, uint32_t b, uint32_t c, uint32_t d) {
    asm volatile("st.global.v4.b32 [%0], {%1, %2, %3, %4};" ::"l"(p), "r"(a), "r"(b), "r"(c), "r"(d) : "memory");
}
__device__ __forceinline__ void lds64(uint32_t addr, uint32_t& a, uint32_t& b) {
    asm volatile("ld.shared.v2.b32 {%0, %1}, [%2];" : "=r"(a), "=r"(b) : "r"(addr) : "memory");
}
__device__ __forceinline__ void lds128(uint32_t addr, uint32_t (&v)[4]) {
    asm volatile("ld.shared.v4.b32 {%0, %1, %2, %3}, [%4];" : "=r"(v[0]), "=r"(v[1]), "=r"(v[2]), "=r"(v[3]) : "r"(addr) : "memory");
}
__device__ __forceinline__ void sts32(uint32_t addr, uint32_t v) { asm volatile("st.shared.b32 [%0], %1;" ::"r"(addr), "r"(v) : "memory"); }
__device__ __forceinline__ void sts128(uint32_t addr, const uint32_t (&v)[4]) {
    asm volatile("st.shared.v4.b32 [%0], {%1, %2, %3, %4};" ::"r"(addr), "r"(v[0]), "r"(v[1]), "r"(v[2]), "r"(v[3]) : "memory");
}
__device__ __forceinline__ void cp16(uint32_t dst, const void* src) {
    asm volatile("cp.async.cg.shared.global [%0], [%1], 16;" ::"r"(dst), "l"(src) : "memory");
}
__device__ __forceinline__ uint32_t prmt(uint32_t a, uint32_t b, uint32_t c) {
    uint32_t d;
    asm("prmt.b32 %0, %1, %2, %3;" : "=r"(d) : "r"(a), "r"(b), "r"(c));
    return d;
}
__device__ __forceinline__ uint32_t pack_bf16(float lo, float hi) {
    uint32_t d;
    asm("cvt.rn.bf16x2.f32 %0, %1, %2;" : "=r"(d) : "f"(hi), "f"(lo));
    return d;
}

template <int OFF, int ACC, int ND>
__device__ __forceinline__ void wgmma_n128(float (&d)[ND], const uint32_t (&a)[4], uint32_t desc_lo) {
    asm volatile("{\n.reg .pred p;\n.reg .b32 lo;\n.reg .b64 db;\n"
        "setp.ne.b32 p, %70, 0;\nadd.u32 lo, %68, %69;\nmov.b64 db, {lo, 0x40000040};\n"
        "wgmma.mma_async.sync.aligned.m64n128k16.f32.bf16.bf16 "
        "{%0, %1, %2, %3, %4, %5, %6, %7, %8, %9, %10, %11, %12, %13, %14, %15, "
        "%16, %17, %18, %19, %20, %21, %22, %23, %24, %25, %26, %27, %28, %29, %30, %31, "
        "%32, %33, %34, %35, %36, %37, %38, %39, %40, %41, %42, %43, %44, %45, %46, %47, "
        "%48, %49, %50, %51, %52, %53, %54, %55, %56, %57, %58, %59, %60, %61, %62, %63}, "
        "{%64, %65, %66, %67}, db, p, 1, 1, 0;\n}\n"
        : "+f"(d[0]), "+f"(d[1]), "+f"(d[2]), "+f"(d[3]), "+f"(d[4]), "+f"(d[5]), "+f"(d[6]), "+f"(d[7]),
          "+f"(d[8]), "+f"(d[9]), "+f"(d[10]), "+f"(d[11]), "+f"(d[12]), "+f"(d[13]), "+f"(d[14]), "+f"(d[15]),
          "+f"(d[16]), "+f"(d[17]), "+f"(d[18]), "+f"(d[19]), "+f"(d[20]), "+f"(d[21]), "+f"(d[22]), "+f"(d[23]),
          "+f"(d[24]), "+f"(d[25]), "+f"(d[26]), "+f"(d[27]), "+f"(d[28]), "+f"(d[29]), "+f"(d[30]), "+f"(d[31]),
          "+f"(d[32]), "+f"(d[33]), "+f"(d[34]), "+f"(d[35]), "+f"(d[36]), "+f"(d[37]), "+f"(d[38]), "+f"(d[39]),
          "+f"(d[40]), "+f"(d[41]), "+f"(d[42]), "+f"(d[43]), "+f"(d[44]), "+f"(d[45]), "+f"(d[46]), "+f"(d[47]),
          "+f"(d[48]), "+f"(d[49]), "+f"(d[50]), "+f"(d[51]), "+f"(d[52]), "+f"(d[53]), "+f"(d[54]), "+f"(d[55]),
          "+f"(d[56]), "+f"(d[57]), "+f"(d[58]), "+f"(d[59]), "+f"(d[60]), "+f"(d[61]), "+f"(d[62]), "+f"(d[63])
        : "r"(a[0]), "r"(a[1]), "r"(a[2]), "r"(a[3]), "r"(desc_lo), "n"(OFF), "n"(ACC));
}
template <int OFF, int ACC, int ND>
__device__ __forceinline__ void wgmma_n96(float (&d)[ND], const uint32_t (&a)[4], uint32_t desc_lo) {
    asm volatile("{\n.reg .pred p;\n.reg .b32 lo;\n.reg .b64 db;\n"
        "setp.ne.b32 p, %54, 0;\nadd.u32 lo, %52, %53;\nmov.b64 db, {lo, 0x40000040};\n"
        "wgmma.mma_async.sync.aligned.m64n96k16.f32.bf16.bf16 "
        "{%0, %1, %2, %3, %4, %5, %6, %7, %8, %9, %10, %11, %12, %13, %14, %15, "
        "%16, %17, %18, %19, %20, %21, %22, %23, %24, %25, %26, %27, %28, %29, %30, %31, "
        "%32, %33, %34, %35, %36, %37, %38, %39, %40, %41, %42, %43, %44, %45, %46, %47}, "
        "{%48, %49, %50, %51}, db, p, 1, 1, 0;\n}\n"
        : "+f"(d[0]), "+f"(d[1]), "+f"(d[2]), "+f"(d[3]), "+f"(d[4]), "+f"(d[5]), "+f"(d[6]), "+f"(d[7]),
          "+f"(d[8]), "+f"(d[9]), "+f"(d[10]), "+f"(d[11]), "+f"(d[12]), "+f"(d[13]), "+f"(d[14]), "+f"(d[15]),
          "+f"(d[16]), "+f"(d[17]), "+f"(d[18]), "+f"(d[19]), "+f"(d[20]), "+f"(d[21]), "+f"(d[22]), "+f"(d[23]),
          "+f"(d[24]), "+f"(d[25]), "+f"(d[26]), "+f"(d[27]), "+f"(d[28]), "+f"(d[29]), "+f"(d[30]), "+f"(d[31]),
          "+f"(d[32]), "+f"(d[33]), "+f"(d[34]), "+f"(d[35]), "+f"(d[36]), "+f"(d[37]), "+f"(d[38]), "+f"(d[39]),
          "+f"(d[40]), "+f"(d[41]), "+f"(d[42]), "+f"(d[43]), "+f"(d[44]), "+f"(d[45]), "+f"(d[46]), "+f"(d[47])
        : "r"(a[0]), "r"(a[1]), "r"(a[2]), "r"(a[3]), "r"(desc_lo), "n"(OFF), "n"(ACC));
}
template <int OFF, int ACC, int ND>
__device__ __forceinline__ void wgmma_n64(float (&d)[ND], const uint32_t (&a)[4], uint32_t desc_lo) {
    asm volatile("{\n.reg .pred p;\n.reg .b32 lo;\n.reg .b64 db;\n"
        "setp.ne.b32 p, %38, 0;\nadd.u32 lo, %36, %37;\nmov.b64 db, {lo, 0x40000040};\n"
        "wgmma.mma_async.sync.aligned.m64n64k16.f32.bf16.bf16 "
        "{%0, %1, %2, %3, %4, %5, %6, %7, %8, %9, %10, %11, %12, %13, %14, %15, "
        "%16, %17, %18, %19, %20, %21, %22, %23, %24, %25, %26, %27, %28, %29, %30, %31}, "
        "{%32, %33, %34, %35}, db, p, 1, 1, 0;\n}\n"
        : "+f"(d[0]), "+f"(d[1]), "+f"(d[2]), "+f"(d[3]), "+f"(d[4]), "+f"(d[5]), "+f"(d[6]), "+f"(d[7]),
          "+f"(d[8]), "+f"(d[9]), "+f"(d[10]), "+f"(d[11]), "+f"(d[12]), "+f"(d[13]), "+f"(d[14]), "+f"(d[15]),
          "+f"(d[16]), "+f"(d[17]), "+f"(d[18]), "+f"(d[19]), "+f"(d[20]), "+f"(d[21]), "+f"(d[22]), "+f"(d[23]),
          "+f"(d[24]), "+f"(d[25]), "+f"(d[26]), "+f"(d[27]), "+f"(d[28]), "+f"(d[29]), "+f"(d[30]), "+f"(d[31])
        : "r"(a[0]), "r"(a[1]), "r"(a[2]), "r"(a[3]), "r"(desc_lo), "n"(OFF), "n"(ACC));
}

template <int V> struct IC { static constexpr int value = V; };
template <int J, int E, class F> __device__ __forceinline__ void static_for(F f) {
    if constexpr (J < E) { f(IC<J>{}); static_for<J + 1, E>(f); }
}

__device__ __forceinline__ void make_lut(uint32_t s2, uint32_t z2, uint32_t (&l)[4]) {
    const __nv_bfloat162 s = *reinterpret_cast<__nv_bfloat162*>(&s2), z = *reinterpret_cast<__nv_bfloat162*>(&z2);
    const uint32_t c01 = 0x3F800000u, c23 = 0x40404000u;
    const __nv_bfloat162 q01 = *reinterpret_cast<const __nv_bfloat162*>(&c01), q23 = *reinterpret_cast<const __nv_bfloat162*>(&c23);
    __nv_bfloat162 r0 = __hmul2_rn(__hsub2_rn(q01, __low2bfloat162(z)), __low2bfloat162(s));
    __nv_bfloat162 r1 = __hmul2_rn(__hsub2_rn(q23, __low2bfloat162(z)), __low2bfloat162(s));
    __nv_bfloat162 r2 = __hmul2_rn(__hsub2_rn(q01, __high2bfloat162(z)), __high2bfloat162(s));
    __nv_bfloat162 r3 = __hmul2_rn(__hsub2_rn(q23, __high2bfloat162(z)), __high2bfloat162(s));
    l[0] = *reinterpret_cast<uint32_t*>(&r0); l[1] = *reinterpret_cast<uint32_t*>(&r1);
    l[2] = *reinterpret_cast<uint32_t*>(&r2); l[3] = *reinterpret_cast<uint32_t*>(&r3);
}
__device__ __forceinline__ uint32_t fields(uint32_t w, uint32_t sh) { return prmt(w >> sh, 0, 0x2200) & 0x0C030C03u; }
__device__ __forceinline__ void selectors(uint32_t m, uint32_t coef, uint32_t bias, uint32_t& s0, uint32_t& s1) {
    asm("dp2a.lo.u32.u32 %0, %1, %2, %3;" : "=r"(s0) : "r"(coef), "r"(m), "r"(bias));
    asm("dp2a.hi.u32.u32 %0, %1, %2, %3;" : "=r"(s1) : "r"(coef), "r"(m), "r"(bias));
}
__device__ __forceinline__ uint32_t bitsel(uint32_t m, uint32_t a, uint32_t b) { return (a & m) | (b & ~m); }
__device__ __forceinline__ void regroup(uint32_t wa, uint32_t wb, uint32_t wc, uint32_t wd, uint32_t (&o)[4]) {
    const uint32_t e_ac = bitsel(0x33333333u, wa, wc << 2), o_ac = bitsel(0x33333333u, wa >> 2, wc);
    const uint32_t e_bd = bitsel(0x33333333u, wb, wd << 2), o_bd = bitsel(0x33333333u, wb >> 2, wd);
    const uint32_t a0 = bitsel(0x0F0F0F0Fu, e_ac, o_bd << 4), a1 = bitsel(0x0F0F0F0Fu, e_ac >> 4, o_bd);
    const uint32_t b0 = bitsel(0x0F0F0F0Fu, e_bd, o_ac << 4), b1 = bitsel(0x0F0F0F0Fu, e_bd >> 4, o_ac);
    o[0] = prmt(a0, b0, 0x6240); o[1] = prmt(a1, b1, 0x6240);
    o[2] = prmt(a0, b0, 0x7351); o[3] = prmt(a1, b1, 0x7351);
}

__global__ void __launch_bounds__(NWG * 128 + 128, 1)
gptq_kernel(const uint8_t* __restrict__ xg, const uint8_t* __restrict__ qw, const uint8_t* __restrict__ sc, const uint8_t* __restrict__ ze,
            const __grid_constant__ CUtensorMap tm_x, const __grid_constant__ CUtensorMap tm_o, const __grid_constant__ CUtensorMap tm_w,
            const __grid_constant__ CUtensorMap tm_x2) {
    extern __shared__ __align__(1024) uint8_t smem_raw[];
    const uint32_t sbase = (uint32_t)__cvta_generic_to_shared(smem_raw);
    const int tid = threadIdx.x;
    const int lane = tid & 31;
    const int g = lane >> 2, t = lane & 3;
    const bool extra = blockIdx.x >= 128;
    const int tt = blockIdx.x >> 3, fs = blockIdx.x & 7;
    const int rbase = extra ? (int)(blockIdx.x - 128) * 512 + 96 : tt * BT, rstep = extra ? 128 : 32;
    auto unit_id = [&](int u, int w) {
        const int k = 3 * u + (u == 2 ? (w == WG96 ? 2 : w == 2 ? WG96 : w) : w);
        return extra ? min(k, 7) * 9 + 8 : fs * 9 + k;
    };
    const uint32_t xbar = sbase + SM_BAR;

    if (tid >= NWG * 128) {
        asm volatile("setmaxnreg.dec.sync.aligned.u32 32;");
        const bool lead = elect_one();
        const int w = __shfl_sync(0xffffffffu, (tid >> 5) & 3, 0);
        const uint32_t full = sbase + SM_FULL + w * 16, empty = sbase + SM_EMPTY + w * 8, staged = sbase + SM_STAGED + w * 8;
        const uint32_t slots = sbase + SM_W + 2 * w * WSLOT;
        auto load_x = [&](int j) {
            mbar_expect_tx(xbar + 8 * j, XBLK);
            tma_load_3d(sbase + SM_X + j * XBLK, extra ? &tm_x2 : &tm_x, j * 64, rbase & 127, rbase >> 7, xbar + 8 * j);
        };
        auto load_raw = [&](int n) {
            mbar_expect_tx(full + (n & 1) * 8, WRAW);
            tma_load_2d(slots + (n & 1) * WSLOT, &tm_w, unit_id(0, w) * 64, n * 12, full + (n & 1) * 8);
        };
        if (lead) {
            if (w < NWG) {
                mbar_init(full, 1);
                mbar_init_fence();
                load_raw(0);
                mbar_init(full + 8, 1);
                mbar_init(empty, 4);
                mbar_init(staged, 4);
                mbar_init(xbar + 8 * (w + 6), 1);
                sts32(sbase + SM_CONST + w * 8, 0x1010u);
                sts32(sbase + SM_CONST + w * 8 + 4, w == 0 ? 0x08800022u : w == 1 ? 0x02200022u : 0x00220220u);
            } else {
                mbar_init(xbar + 8, 1);
                mbar_init_fence();
                load_x(1);
                mbar_init(xbar, 256);
                sts32(sbase + SM_CONST + 24, 0x3F800000u);
#pragma unroll
                for (int j = 2; j < 6; j++) mbar_init(xbar + 8 * j, 1);
            }
            mbar_init_fence();
        }
        __syncthreads();
        if (lead) {
            if (w < NWG) load_raw(1);
            else { load_x(2); load_x(3); }
        }
        __syncwarp();
        const int item = (tt & 15) * 108 + min(tid - NWG * 128, 107);
        const int prow = item >> 5, pair = item & 31;
        const int uu = prow / 9 + 3, pj = prow % 9;
        const uint32_t pcol = fs * 576 + uu * 64 + pair * 2;
        uint32_t q[4][2];
#pragma unroll
        for (int i = 0; i < 4; i++) ldg64(qw + (uint32_t)(((4 * pj + i) * F_N + pcol) * 4), q[i][0], q[i][1]);
        const uint32_t s2 = ldg32(sc + (uint32_t)((pj * F_N + pcol) * 2));
        const uint32_t z2 = ldg32(ze + (uint32_t)((pj * F_N + pcol) * 2));
        if (w == NWG) {
            mbar_wait(xbar, 0);
            if (lead) {
#pragma unroll
                for (int j = 4; j < NGRP; j++) load_x(j);
                asm volatile("prefetch.tensormap [%0];" ::"l"(&tm_o) : "memory");
            }
            __syncwarp();
        }
        if (!extra) {
            uint32_t o0[4], o1[4], l[4];
            uint8_t* dst = g_prep + ((fs * 9 + uu) * 3 + pj / 3) * WSLOT;
            regroup(q[0][0], q[1][0], q[2][0], q[3][0], o0);
            regroup(q[0][1], q[1][1], q[2][1], q[3][1], o1);
            make_lut(s2, z2, l);
            stg128(dst + (pj % 3) * 1024 + pair * 32, o0[0], o1[0], o0[1], o1[1]);
            stg128(dst + (pj % 3) * 1024 + pair * 32 + 16, o0[2], o1[2], o0[3], o1[3]);
            stg128(dst + WRAW + (pj % 3) * 512 + pair * 16, l[0], l[1], l[2], l[3]);
        }
        bar_sync(10, 128);
        if (w == NWG) {
            if (extra ? lane < 8 : lead) {
                uint32_t* ready = &g_ready[(extra ? lane : fs) * 32];
                __threadfence();
                const uint32_t target = (atomicAdd(ready, extra ? 4u : 1u) & ~31u) + 32u;
                uint32_t seen, spins = 0;
                do {
                    asm volatile("ld.acquire.gpu.global.u32 %0, [%1];" : "=r"(seen) : "l"(ready) : "memory");
                    if (++spins > 0x400000u) __trap();
                } while ((int32_t)(seen - target) < 0);
            }
            __syncwarp();
        } else {
            mbar_wait(empty, 0);
            if (lead) load_raw(2);
            __syncwarp();
        }
        bar_sync(10, 128);
        if (w < NWG && lead) {
            asm volatile("fence.proxy.async.global;" ::: "memory");
#pragma unroll 1
            for (int n = 1; n < 8; n++) {
                mbar_wait(empty, n & 1);
                if (n % 3 == 1) bulk_wait_read();
                if (n < 7) {
                    mbar_expect_tx(full + (n & 1) * 8, WSLOT);
                    bulk_load(slots + (n & 1) * WSLOT, g_prep + (unit_id((n + 2) / 3, w) * 3 + (n + 2) % 3) * WSLOT, WSLOT, full + (n & 1) * 8);
                } else {
                    mbar_arrive(full + (n & 1) * 8);
                }
                if (n % 3 == 0) {
                    mbar_wait(staged, (n / 3 - 1) & 1);
#pragma unroll
                    for (int p = 0; p < 4; p++)
                        tma_store_2d(&tm_o, unit_id(n / 3 - 1, w) * 64, rbase + p * rstep, sbase + SM_O + w * 16384 + 4096 * p);
                    bulk_commit();
                }
            }
        }
        return;
    }

    const int lrow = min(lane >> 3, 2);
    const int colt = unit_id(0, tid >> 7) * 64 + ((tid >> 5) & 3) * 16;
    const uint8_t* ssrc = sc + (uint32_t)(2 * (lrow * F_N + colt + (lane & 7) * 2));
    const uint8_t* zsrc = ze + (uint32_t)(2 * (lrow * F_N + colt + (lane & 7) * 2));
    uint32_t W0[4][2], s_in[3], z_in[3];
#pragma unroll
    for (int i = 0; i < 4; i++) ldg64(qw + (uint32_t)((colt + 2 * g) * 4) + i * F_N * 4, W0[i][0], W0[i][1]);
    s_in[0] = ldg32(ssrc);
    z_in[0] = ldg32(zsrc);
    if (tid < 256) {
        const uint8_t* xsrc = xg + (uint32_t)((rbase + (tid >> 3)) * (D_K * 2) + (tid & 7) * 16);
        const uint32_t xdst = sbase + SM_X + (tid >> 3) * 128 + (((tid & 7) ^ ((tid >> 3) & 7)) << 4);
#pragma unroll
        for (int i = 0; i < 4; i++) cp16(xdst + i * 4096, xsrc + (uint32_t)(i * rstep * (D_K * 2)));
    }
    const int wid = __shfl_sync(0xffffffffu, tid >> 5, 0);
    const int wg = wid >> 2, warp = wid & 3;
    asm volatile("setmaxnreg.inc.sync.aligned.u32 160;");
    __syncthreads();
    if (tid < 256) asm volatile("cp.async.mbarrier.arrive.noinc.shared::cta.b64 [%0];" ::"r"(xbar) : "memory");

    uint32_t coef, bias, coefA, biasA, coefB, biasB;
    lds64(sbase + SM_CONST, bias, coef);
    const uint32_t sh = 4 * t;
    const uint32_t desc0 = (((sbase + SM_X) & 0x3FFFFu) >> 4) | (1u << 16);
    const uint32_t obuf = sbase + SM_O + wg * 16384;
    const uint32_t st_addr0 = obuf + (2 * t) * 128 + (((2 * warp + (g >> 2)) ^ (2 * t)) << 4) + (g & 3) * 4;
    const uint32_t st_addr1 = obuf + (2 * t + 1) * 128 + (((2 * warp + (g >> 2)) ^ (2 * t + 1)) << 4) + (g & 3) * 4;
    const uint32_t slots = sbase + SM_W + wg * 2 * WSLOT;
    const uint32_t full = sbase + SM_FULL + wg * 16, empty = sbase + SM_EMPTY + wg * 8, staged = sbase + SM_STAGED + wg * 8;
    const uint32_t l_ld = slots + WRAW + warp * 128 + g * 16;
    const uint32_t p_ld = slots + warp * 256 + lane * 8;

    float acc[64];
    uint32_t A[2][4][4], S[4][4], P[32], lut[4];
    auto lookup = [&](const uint32_t (&sel)[4][4], uint32_t (&dst)[4][4]) {
#pragma unroll
        for (int i = 0; i < 4; i++)
#pragma unroll
            for (int r = 0; r < 4; r++) dst[i][r] = prmt(lut[2 - 2 * (r & 1)], lut[3 - 2 * (r & 1)], sel[i][r]);
    };
    auto mma_group = [&](auto nc, auto jc, const uint32_t (&a)[4][4]) {
        constexpr int j = decltype(jc)::value;
        wg_fence();
        static_for<0, 4>([&](auto ic) {
            constexpr int i = decltype(ic)::value;
            if constexpr (decltype(nc)::value == 128) wgmma_n128<j * (XBLK >> 4) + 2 * i, (j + i > 0)>(acc, a[i], desc0);
            else wgmma_n96<j * (XBLK >> 4) + 2 * i, (j + i > 0)>(acc, a[i], desc0);
        });
        wg_commit();
    };
    auto next_third = [&](int n) {
        mbar_wait(full + 8 * ((n + 1) & 1), ((n + 1) >> 1) & 1);
        if (elect_one()) mbar_arrive(empty);
        __syncwarp();
    };
    auto pack_unit = [&]() {
#pragma unroll
        for (int i = 0; i < 16; i++) {
            P[2 * i] = pack_bf16(acc[4 * i + 2], acc[4 * i + 0]);
            P[2 * i + 1] = pack_bf16(acc[4 * i + 3], acc[4 * i + 1]);
        }
    };
    auto raw_selectors = [&](const uint32_t (&W)[4][2], uint32_t (&sel)[4][4]) {
#pragma unroll
        for (int i = 0; i < 4; i++) {
            selectors(fields(W[i][1], sh), coef, bias, sel[i][0], sel[i][2]);
            selectors(fields(W[i][0], sh), coef, bias, sel[i][1], sel[i][3]);
        }
    };
    auto prep_selectors = [&](uint32_t w0, uint32_t w1, uint32_t (&sel)[4][4]) {
#pragma unroll
        for (int r = 0; r < 2; r++) {
            const uint32_t w = r ? w0 : w1, v = w >> 2;
            selectors(w & 0x30033003u, coefA, biasA, sel[0][r], sel[0][r + 2]);
            selectors(v & 0x30033003u, coefA, biasA, sel[2][r], sel[2][r + 2]);
            selectors(w & 0x03300330u, coefB, biasA, sel[1][r], sel[1][r + 2]);
            selectors(v & 0x03300330u, coefB, biasA, sel[3][r], sel[3][r + 2]);
        }
    };

    {
        const uint32_t w_ld = slots + warp * 64 + g * 8;
        const uint32_t l_st = slots + WRAW + lrow * 512 + warp * 128 + (lane & 7) * 16;
        auto build_table = [&](int r) {
            uint32_t l[4];
            make_lut(s_in[r], z_in[r], l);
            sts128(l_st + (r & 1) * WSLOT, l);
            __syncwarp();
        };
        build_table(0);
        lds128(l_ld, lut);
        raw_selectors(W0, S);
        lookup(S, A[0]);
        if (wg > 0) bar_sync(7 + wg, 256);
        static_for<0, NGRP>([&](auto jc) {
            constexpr int j = decltype(jc)::value;
            mbar_wait(xbar + 8 * j, 0);
            if (j == 0) proxy_fence_shared();
            mma_group(IC<128>{}, jc, A[j % 2]);
            if (j == 0) {
                if (wg < 2) bar_arrive(8 + wg, 256);
#pragma unroll
                for (int r = 1; r < 3; r++) { s_in[r] = ldg32(ssrc + 3 * r * F_N * 2); z_in[r] = ldg32(zsrc + 3 * r * F_N * 2); }
                mbar_wait(full, 0);
            }
            if (j == 2) { build_table(1); build_table(2); }
            if (j % 3 == 2) next_third(j / 3);
            if (j + 1 < NGRP) {
                uint32_t W[4][2], T[4][4];
                const int so = (((j + 1) / 3) & 1) * WSLOT;
#pragma unroll
                for (int i = 0; i < 4; i++) lds64(w_ld + so + (((j + 1) % 3) * 4 + i) * 256, W[i][0], W[i][1]);
                wg_wait<1>();
                __syncwarp();
                lds128(l_ld + so + ((j + 1) % 3) * 512, lut);
                raw_selectors(W, T);
                lookup(T, A[(j + 1) % 2]);
            }
        });
        uint32_t w0, w1;
        lds64(sbase + SM_CONST + 8, biasA, coefA);
        lds64(sbase + SM_CONST + 16, biasB, coefB);
        lds128(l_ld + WSLOT, lut);
        lds64(p_ld + WSLOT, w0, w1);
        prep_selectors(w0, w1, S);
        wg_wait<0>();
        pack_unit();
    }

    auto group = [&](auto nc, auto uc, auto jc) {
        constexpr int u = decltype(uc)::value, j = decltype(jc)::value;
        if (j == 0) lookup(S, A[0]);
        if (u == 1 && j == 1 && wg == 2) bar_sync(11, 256);
        if (u == 1 && j == 6 && wg == 1) bar_sync(12, 256);
        mma_group(nc, jc, A[j % 2]);
        if (u == 1 && j == 6 && wg == 0) bar_arrive(11, 256);
        if (u == 1 && j == 8 && wg == 0) bar_arrive(12, 256);
        if (j == 3) {
            proxy_fence_shared();
            __syncwarp();
            if (elect_one()) mbar_arrive(staged);
            __syncwarp();
        }
        if (j % 3 == 2) next_third(3 * u + j / 3);
        uint32_t w0, w1;
        constexpr int so = ((3 * u + (j + 1) / 3) & 1) * WSLOT;
        if (j + 1 == NGRP) lds128(l_ld + so, lut);
        lds64(p_ld + so + ((j + 1) % 3) * 1024, w0, w1);
        if (j < 3) {
#pragma unroll
            for (int i = (j == 0 ? 0 : j == 1 ? 6 : 11); i < (j == 0 ? 6 : j == 1 ? 11 : 16); i++) {
                sts32(st_addr0 + i * 1024, P[2 * i]);
                sts32(st_addr1 + i * 1024, P[2 * i + 1]);
            }
        }
        if (j + 1 < NGRP) {
            uint32_t T[4][4];
            wg_wait<1>();
            __syncwarp();
            lds128(l_ld + so + ((j + 1) % 3) * 512, lut);
            prep_selectors(w0, w1, T);
            lookup(T, A[(j + 1) % 2]);
        } else {
            prep_selectors(w0, w1, S);
            wg_wait<0>();
            pack_unit();
        }
    };
    auto store_rows = [&](auto q0c, auto q1c, const float* d, int issuer, bool keep) {
        constexpr int q0 = decltype(q0c)::value, q1 = decltype(q1c)::value;
#pragma unroll
        for (int i = 0; i < 4 * (q1 - q0); i++) {
            sts32(st_addr0 + (4 * q0 + i) * 1024, pack_bf16(d[4 * i + 2], d[4 * i + 0]));
            sts32(st_addr1 + (4 * q0 + i) * 1024, pack_bf16(d[4 * i + 3], d[4 * i + 1]));
        }
        proxy_fence_shared();
        bar_sync(1 + wg, 128);
        if (warp == issuer && keep) {
            if (elect_one()) {
#pragma unroll
                for (int q = q0; q < q1; q++) tma_store_2d(&tm_o, unit_id(2, wg) * 64, rbase + q * rstep, obuf + 4096 * q);
                bulk_commit();
            }
            __syncwarp();
        }
    };

    static_for<0, 9>([&](auto jc) { group(IC<128>{}, IC<1>{}, jc); });
    if (wg == WG96) {
        static_for<0, 8>([&](auto jc) { group(IC<96>{}, IC<2>{}, jc); });
        mma_group(IC<96>{}, IC<8>{}, A[0]);
        mbar_wait(full + 8, 0);
        wg_wait<0>();
        store_rows(IC<0>{}, IC<2>{}, acc, 0, !extra);
        store_rows(IC<2>{}, IC<3>{}, acc + 32, 1, !extra);
    } else {
        static_for<0, 7>([&](auto jc) { group(IC<128>{}, IC<2>{}, jc); });
        uint32_t w0, w1;
        lds64(p_ld + 2 * 1024, w0, w1);
        prep_selectors(w0, w1, S);
        mbar_wait(full + 8, 0);
        wg_wait<0>();
        float lo[32], hi[32];
#pragma unroll
        for (int i = 0; i < 32; i++) lo[i] = acc[i];
        auto part = [&](float (&d)[32], auto hc, auto jc) {
            static_for<0, 4>([&](auto ic) {
                constexpr int i = decltype(ic)::value, j = decltype(jc)::value;
                wgmma_n64<j * (XBLK >> 4) + 2 * i + decltype(hc)::value * 512, 1>(d, A[j % 2][i], desc0);
            });
        };
        wg_fence();
        part(lo, IC<0>{}, IC<7>{});
        wg_commit();
        __syncwarp();
        lds128(l_ld + 2 * 512, lut);
        lookup(S, A[0]);
        wg_fence();
        part(lo, IC<0>{}, IC<8>{});
        wg_commit();
        __syncwarp();
        lds64(sbase + SM_CONST + 24, w0, w1);
#pragma unroll
        for (int i = 0; i < 32; i++) hi[i] = acc[32 + i] * __uint_as_float(w0);
        wg_fence();
        part(hi, IC<1>{}, IC<7>{});
        part(hi, IC<1>{}, IC<8>{});
        wg_commit();
        wg_wait<1>();
        store_rows(IC<0>{}, IC<2>{}, lo, 0, true);
        wg_wait<0>();
        store_rows(IC<2>{}, IC<4>{}, hi, 1, true);
    }
    bulk_wait_read();
}

__global__ void gptq_fallback(const __nv_bfloat16* __restrict__ x, const uint32_t* __restrict__ qw, const __nv_bfloat16* __restrict__ sc,
                              const __nv_bfloat16* __restrict__ ze, __nv_bfloat16* __restrict__ out) {
    const int f = blockIdx.x * blockDim.x + threadIdx.x, t0 = blockIdx.y * 8;
    float acc[8] = {};
    for (int k = 0; k < D_K; k++) {
        const float q = (float)((qw[(k >> 4) * F_N + f] >> (2 * (k & 15))) & 3u);
        const __nv_bfloat16 d = __float2bfloat16(q - __bfloat162float(ze[(k >> 6) * F_N + f]));
        const float w = __bfloat162float(__float2bfloat16(__bfloat162float(d) * __bfloat162float(sc[(k >> 6) * F_N + f])));
#pragma unroll
        for (int i = 0; i < 8; i++) acc[i] = fmaf(__bfloat162float(x[(t0 + i) * D_K + k]), w, acc[i]);
    }
#pragma unroll
    for (int i = 0; i < 8; i++) out[(size_t)(t0 + i) * F_N + f] = __float2bfloat16(acc[i]);
}

typedef CUresult (*EncodeFn)(CUtensorMap*, CUtensorMapDataType, cuuint32_t, void*, const cuuint64_t*, const cuuint64_t*,
                             const cuuint32_t*, const cuuint32_t*, CUtensorMapInterleave, CUtensorMapSwizzle,
                             CUtensorMapL2promotion, CUtensorMapFloatOOBfill);

}


extern "C" void kernel_launch(void* const* d_in, const int* in_sizes, int n_in, void* d_out, int out_size) {
    static EncodeFn encode = nullptr;
    static int resident = -1;
    if (resident < 0) {
        void* fn = nullptr;
        cudaDriverEntryPointQueryResult qr;
        cudaGetDriverEntryPoint("cuTensorMapEncodeTiled", &fn, cudaEnableDefault, &qr);
        encode = (EncodeFn)fn;
        cudaFuncSetAttribute(gptq_kernel, cudaFuncAttributeMaxDynamicSharedMemorySize, SM_TOTAL);
        int dev = 0, sms = 0, per_sm = 0;
        cudaGetDevice(&dev);
        cudaDeviceGetAttribute(&sms, cudaDevAttrMultiProcessorCount, dev);
        cudaOccupancyMaxActiveBlocksPerMultiprocessor(&per_sm, gptq_kernel, NWG * 128 + 128, SM_TOTAL);
        resident = sms * per_sm;
    }
    if (!encode || resident < GRID) {
        gptq_fallback<<<dim3(F_N / 128, S_TOK / 8), 128, 0, cudaStreamPerThread>>>(
            (const __nv_bfloat16*)d_in[0], (const uint32_t*)d_in[1], (const __nv_bfloat16*)d_in[2], (const __nv_bfloat16*)d_in[3],
            (__nv_bfloat16*)d_out);
        return;
    }
    CUtensorMap tm_x, tm_o, tm_w, tm_x2;
    for (int v = 0; v < 2; v++) {
        cuuint64_t dims[3] = {D_K, BT, S_TOK / BT}, strides[2] = {D_K * 2, D_K * 2 * BT};
        cuuint32_t box[3] = {64, v ? 32u : 128u, v ? 4u : 1u}, es[3] = {1, 1, 1};
        encode(v ? &tm_x2 : &tm_x, CU_TENSOR_MAP_DATA_TYPE_BFLOAT16, 3, d_in[0], dims, strides, box, es, CU_TENSOR_MAP_INTERLEAVE_NONE,
               CU_TENSOR_MAP_SWIZZLE_128B, CU_TENSOR_MAP_L2_PROMOTION_L2_128B, CU_TENSOR_MAP_FLOAT_OOB_FILL_NONE);
    }
    {
        cuuint64_t dims[2] = {F_N, S_TOK}, strides[1] = {F_N * 2};
        cuuint32_t box[2] = {64, 32}, es[2] = {1, 1};
        encode(&tm_o, CU_TENSOR_MAP_DATA_TYPE_BFLOAT16, 2, d_out, dims, strides, box, es, CU_TENSOR_MAP_INTERLEAVE_NONE,
               CU_TENSOR_MAP_SWIZZLE_128B, CU_TENSOR_MAP_L2_PROMOTION_NONE, CU_TENSOR_MAP_FLOAT_OOB_FILL_NONE);
    }
    {
        cuuint64_t dims[2] = {F_N, 36}, strides[1] = {F_N * 4};
        cuuint32_t box[2] = {64, 12}, es[2] = {1, 1};
        encode(&tm_w, CU_TENSOR_MAP_DATA_TYPE_INT32, 2, d_in[1], dims, strides, box, es, CU_TENSOR_MAP_INTERLEAVE_NONE,
               CU_TENSOR_MAP_SWIZZLE_NONE, CU_TENSOR_MAP_L2_PROMOTION_L2_128B, CU_TENSOR_MAP_FLOAT_OOB_FILL_NONE);
    }
    gptq_kernel<<<GRID, NWG * 128 + 128, SM_TOTAL, cudaStreamPerThread>>>(
        (const uint8_t*)d_in[0], (const uint8_t*)d_in[1], (const uint8_t*)d_in[2], (const uint8_t*)d_in[3], tm_x, tm_o, tm_w, tm_x2);
}
```

```cpp
#include <cuda_runtime.h>
#include <cuda_bf16.h>
#include <cuda.h>
#include <stdint.h>

namespace {

constexpr int S_TOK = 2048, D_K = 576, F_N = 4608, NGRP = 9;
constexpr int BT = 128;
constexpr int NWG = 3;
constexpr int GRID = 132;
constexpr int WG96 = 1;
constexpr int XBLK = BT * 128;
constexpr int WRAW = 12 * 256;
constexpr int WSLOT = WRAW + 3 * 512;
constexpr int SM_X = 0;
constexpr int SM_O = NGRP * XBLK;
constexpr int SM_W = SM_O + NWG * 16384;
constexpr int SM_BAR = SM_W + NWG * 2 * WSLOT;
constexpr int SM_FULL = SM_BAR + 80;
constexpr int SM_EMPTY = SM_FULL + NWG * 16;
constexpr int SM_STAGED = SM_EMPTY + NWG * 8;
constexpr int SM_CONST = SM_STAGED + NWG * 8;
constexpr int SM_TOTAL = SM_CONST + 32;

__device__ __align__(128) uint8_t g_prep[72 * 3 * WSLOT];
__device__ uint32_t g_ready[8 * 32];


__device__ __forceinline__ void mbar_init(uint32_t bar, uint32_t cnt) {
    asm volatile("mbarrier.init.shared::cta.b64 [%0], %1;" ::"r"(bar), "r"(cnt));
}
__device__ __forceinline__ void mbar_init_fence() { asm volatile("fence.mbarrier_init.release.cluster;" ::: "memory"); }
__device__ __forceinline__ void mbar_expect_tx(uint32_t bar, uint32_t bytes) {
    asm volatile("mbarrier.arrive.expect_tx.shared::cta.b64 _, [%0], %1;" ::"r"(bar), "r"(bytes) : "memory");
}
__device__ __forceinline__ void mbar_arrive(uint32_t bar) {
    asm volatile("mbarrier.arrive.shared::cta.b64 _, [%0];" ::"r"(bar) : "memory");
}
__device__ __forceinline__ void mbar_wait(uint32_t bar, uint32_t parity) {
    asm volatile("{\n.reg .pred p;\n.reg .u32 c;\n"
                 "mbarrier.try_wait.parity.shared::cta.b64 p, [%0], %1;\n"
                 "@p bra LAB_DONE;\n"
                 "mov.u32 c, 0;\n"
                 "LAB_WAIT:\n"
                 "mbarrier.try_wait.parity.shared::cta.b64 p, [%0], %1;\n"
                 "@p bra LAB_DONE;\n"
                 "add.u32 c, c, 1;\n"
                 "setp.lt.u32 p, c, 0x400000;\n"
                 "@p bra LAB_WAIT;\n"
                 "trap;\n"
                 "LAB_DONE:\n}\n" ::"r"(bar), "r"(parity) : "memory");
}
__device__ __forceinline__ void tma_load_2d(uint32_t dst, const CUtensorMap* m, int c0, int c1, uint32_t bar) {
    asm volatile("cp.async.bulk.tensor.2d.shared::cluster.global.mbarrier::complete_tx::bytes [%0], [%1, {%3, %4}], [%2];"
                 ::"r"(dst), "l"(m), "r"(bar), "r"(c0), "r"(c1) : "memory");
}
__device__ __forceinline__ void tma_load_3d(uint32_t dst, const CUtensorMap* m, int c0, int c1, int c2, uint32_t bar) {
    asm volatile("cp.async.bulk.tensor.3d.shared::cluster.global.mbarrier::complete_tx::bytes [%0], [%1, {%3, %4, %5}], [%2];"
                 ::"r"(dst), "l"(m), "r"(bar), "r"(c0), "r"(c1), "r"(c2) : "memory");
}
__device__ __forceinline__ void tma_store_2d(const CUtensorMap* m, int c0, int c1, uint32_t src) {
    asm volatile("cp.async.bulk.tensor.2d.global.shared::cta.bulk_group [%0, {%2, %3}], [%1];"
                 ::"l"(m), "r"(src), "r"(c0), "r"(c1) : "memory");
}
__device__ __forceinline__ void bulk_load(uint32_t dst, const void* src, uint32_t bytes, uint32_t bar) {
    asm volatile("cp.async.bulk.shared::cluster.global.mbarrier::complete_tx::bytes [%0], [%1], %2, [%3];"
                 ::"r"(dst), "l"(src), "r"(bytes), "r"(bar) : "memory");
}
__device__ __forceinline__ void bulk_commit() { asm volatile("cp.async.bulk.commit_group;" ::: "memory"); }
__device__ __forceinline__ void bulk_wait_read() { asm volatile("cp.async.bulk.wait_group.read 0;" ::: "memory"); }
__device__ __forceinline__ void proxy_fence_shared() { asm volatile("fence.proxy.async.shared::cta;" ::: "memory"); }
__device__ __forceinline__ bool elect_one() {
    uint32_t p;
    asm volatile("{\n.reg .pred q;\nelect.sync _|q, 0xffffffff;\nselp.b32 %0, 1, 0, q;\n}\n" : "=r"(p));
    return p != 0;
}
__device__ __forceinline__ void wg_fence() { asm volatile("wgmma.fence.sync.aligned;" ::: "memory"); }
__device__ __forceinline__ void wg_commit() { asm volatile("wgmma.commit_group.sync.aligned;" ::: "memory"); }
template <int N> __device__ __forceinline__ void wg_wait() { asm volatile("wgmma.wait_group.sync.aligned %0;" ::"n"(N) : "memory"); }
__device__ __forceinline__ void bar_sync(int id, int n) { asm volatile("bar.sync %0, %1;" ::"r"(id), "r"(n) : "memory"); }
__device__ __forceinline__ void bar_arrive(int id, int n) { asm volatile("bar.arrive %0, %1;" ::"r"(id), "r"(n) : "memory"); }
__device__ __forceinline__ uint32_t ldg32(const void* p) {
    uint32_t v;
    asm volatile("ld.global.nc.b32 %0, [%1];" : "=r"(v) : "l"(p));
    return v;
}
__device__ __forceinline__ void ldg64(const void* p, uint32_t& a, uint32_t& b) {
    asm volatile("ld.global.nc.v2.b32 {%0, %1}, [%2];" : "=r"(a), "=r"(b) : "l"(p));
}
__device__ __forceinline__ void stg128(void* p, uint32_t a, uint32_t b, uint32_t c, uint32_t d) {
    asm volatile("st.global.v4.b32 [%0], {%1, %2, %3, %4};" ::"l"(p), "r"(a), "r"(b), "r"(c), "r"(d) : "memory");
}
__device__ __forceinline__ void lds64(uint32_t addr, uint32_t& a, uint32_t& b) {
    asm volatile("ld.shared.v2.b32 {%0, %1}, [%2];" : "=r"(a), "=r"(b) : "r"(addr) : "memory");
}
__device__ __forceinline__ void lds128(uint32_t addr, uint32_t (&v)[4]) {
    asm volatile("ld.shared.v4.b32 {%0, %1, %2, %3}, [%4];" : "=r"(v[0]), "=r"(v[1]), "=r"(v[2]), "=r"(v[3]) : "r"(addr) : "memory");
}
__device__ __forceinline__ void sts32(uint32_t addr, uint32_t v) { asm volatile("st.shared.b32 [%0], %1;" ::"r"(addr), "r"(v) : "memory"); }
__device__ __forceinline__ void sts128(uint32_t addr, const uint32_t (&v)[4]) {
    asm volatile("st.shared.v4.b32 [%0], {%1, %2, %3, %4};" ::"r"(addr), "r"(v[0]), "r"(v[1]), "r"(v[2]), "r"(v[3]) : "memory");
}
__device__ __forceinline__ void cp16(uint32_t dst, const void* src) {
    asm volatile("cp.async.cg.shared.global [%0], [%1], 16;" ::"r"(dst), "l"(src) : "memory");
}
__device__ __forceinline__ uint32_t prmt(uint32_t a, uint32_t b, uint32_t c) {
    uint32_t d;
    asm("prmt.b32 %0, %1, %2, %3;" : "=r"(d) : "r"(a), "r"(b), "r"(c));
    return d;
}
__device__ __forceinline__ uint32_t pack_bf16(float lo, float hi) {
    uint32_t d;
    asm("cvt.rn.bf16x2.f32 %0, %1, %2;" : "=r"(d) : "f"(hi), "f"(lo));
    return d;
}

template <int OFF, int ACC, int ND>
__device__ __forceinline__ void wgmma_n128(float (&d)[ND], const uint32_t (&a)[4], uint32_t desc_lo) {
    asm volatile("{\n.reg .pred p;\n.reg .b32 lo;\n.reg .b64 db;\n"
        "setp.ne.b32 p, %70, 0;\nadd.u32 lo, %68, %69;\nmov.b64 db, {lo, 0x40000040};\n"
        "wgmma.mma_async.sync.aligned.m64n128k16.f32.bf16.bf16 "
        "{%0, %1, %2, %3, %4, %5, %6, %7, %8, %9, %10, %11, %12, %13, %14, %15, "
        "%16, %17, %18, %19, %20, %21, %22, %23, %24, %25, %26, %27, %28, %29, %30, %31, "
        "%32, %33, %34, %35, %36, %37, %38, %39, %40, %41, %42, %43, %44, %45, %46, %47, "
        "%48, %49, %50, %51, %52, %53, %54, %55, %56, %57, %58, %59, %60, %61, %62, %63}, "
        "{%64, %65, %66, %67}, db, p, 1, 1, 0;\n}\n"
        : "+f"(d[0]), "+f"(d[1]), "+f"(d[2]), "+f"(d[3]), "+f"(d[4]), "+f"(d[5]), "+f"(d[6]), "+f"(d[7]),
          "+f"(d[8]), "+f"(d[9]), "+f"(d[10]), "+f"(d[11]), "+f"(d[12]), "+f"(d[13]), "+f"(d[14]), "+f"(d[15]),
          "+f"(d[16]), "+f"(d[17]), "+f"(d[18]), "+f"(d[19]), "+f"(d[20]), "+f"(d[21]), "+f"(d[22]), "+f"(d[23]),
          "+f"(d[24]), "+f"(d[25]), "+f"(d[26]), "+f"(d[27]), "+f"(d[28]), "+f"(d[29]), "+f"(d[30]), "+f"(d[31]),
          "+f"(d[32]), "+f"(d[33]), "+f"(d[34]), "+f"(d[35]), "+f"(d[36]), "+f"(d[37]), "+f"(d[38]), "+f"(d[39]),
          "+f"(d[40]), "+f"(d[41]), "+f"(d[42]), "+f"(d[43]), "+f"(d[44]), "+f"(d[45]), "+f"(d[46]), "+f"(d[47]),
          "+f"(d[48]), "+f"(d[49]), "+f"(d[50]), "+f"(d[51]), "+f"(d[52]), "+f"(d[53]), "+f"(d[54]), "+f"(d[55]),
          "+f"(d[56]), "+f"(d[57]), "+f"(d[58]), "+f"(d[59]), "+f"(d[60]), "+f"(d[61]), "+f"(d[62]), "+f"(d[63])
        : "r"(a[0]), "r"(a[1]), "r"(a[2]), "r"(a[3]), "r"(desc_lo), "n"(OFF), "n"(ACC));
}
template <int OFF, int ACC, int ND>
__device__ __forceinline__ void wgmma_n96(float (&d)[ND], const uint32_t (&a)[4], uint32_t desc_lo) {
    asm volatile("{\n.reg .pred p;\n.reg .b32 lo;\n.reg .b64 db;\n"
        "setp.ne.b32 p, %54, 0;\nadd.u32 lo, %52, %53;\nmov.b64 db, {lo, 0x40000040};\n"
        "wgmma.mma_async.sync.aligned.m64n96k16.f32.bf16.bf16 "
        "{%0, %1, %2, %3, %4, %5, %6, %7, %8, %9, %10, %11, %12, %13, %14, %15, "
        "%16, %17, %18, %19, %20, %21, %22, %23, %24, %25, %26, %27, %28, %29, %30, %31, "
        "%32, %33, %34, %35, %36, %37, %38, %39, %40, %41, %42, %43, %44, %45, %46, %47}, "
        "{%48, %49, %50, %51}, db, p, 1, 1, 0;\n}\n"
        : "+f"(d[0]), "+f"(d[1]), "+f"(d[2]), "+f"(d[3]), "+f"(d[4]), "+f"(d[5]), "+f"(d[6]), "+f"(d[7]),
          "+f"(d[8]), "+f"(d[9]), "+f"(d[10]), "+f"(d[11]), "+f"(d[12]), "+f"(d[13]), "+f"(d[14]), "+f"(d[15]),
          "+f"(d[16]), "+f"(d[17]), "+f"(d[18]), "+f"(d[19]), "+f"(d[20]), "+f"(d[21]), "+f"(d[22]), "+f"(d[23]),
          "+f"(d[24]), "+f"(d[25]), "+f"(d[26]), "+f"(d[27]), "+f"(d[28]), "+f"(d[29]), "+f"(d[30]), "+f"(d[31]),
          "+f"(d[32]), "+f"(d[33]), "+f"(d[34]), "+f"(d[35]), "+f"(d[36]), "+f"(d[37]), "+f"(d[38]), "+f"(d[39]),
          "+f"(d[40]), "+f"(d[41]), "+f"(d[42]), "+f"(d[43]), "+f"(d[44]), "+f"(d[45]), "+f"(d[46]), "+f"(d[47])
        : "r"(a[0]), "r"(a[1]), "r"(a[2]), "r"(a[3]), "r"(desc_lo), "n"(OFF), "n"(ACC));
}
template <int OFF, int ACC, int ND>
__device__ __forceinline__ void wgmma_n64(float (&d)[ND], const uint32_t (&a)[4], uint32_t desc_lo) {
    asm volatile("{\n.reg .pred p;\n.reg .b32 lo;\n.reg .b64 db;\n"
        "setp.ne.b32 p, %38, 0;\nadd.u32 lo, %36, %37;\nmov.b64 db, {lo, 0x40000040};\n"
        "wgmma.mma_async.sync.aligned.m64n64k16.f32.bf16.bf16 "
        "{%0, %1, %2, %3, %4, %5, %6, %7, %8, %9, %10, %11, %12, %13, %14, %15, "
        "%16, %17, %18, %19, %20, %21, %22, %23, %24, %25, %26, %27, %28, %29, %30, %31}, "
        "{%32, %33, %34, %35}, db, p, 1, 1, 0;\n}\n"
        : "+f"(d[0]), "+f"(d[1]), "+f"(d[2]), "+f"(d[3]), "+f"(d[4]), "+f"(d[5]), "+f"(d[6]), "+f"(d[7]),
          "+f"(d[8]), "+f"(d[9]), "+f"(d[10]), "+f"(d[11]), "+f"(d[12]), "+f"(d[13]), "+f"(d[14]), "+f"(d[15]),
          "+f"(d[16]), "+f"(d[17]), "+f"(d[18]), "+f"(d[19]), "+f"(d[20]), "+f"(d[21]), "+f"(d[22]), "+f"(d[23]),
          "+f"(d[24]), "+f"(d[25]), "+f"(d[26]), "+f"(d[27]), "+f"(d[28]), "+f"(d[29]), "+f"(d[30]), "+f"(d[31])
        : "r"(a[0]), "r"(a[1]), "r"(a[2]), "r"(a[3]), "r"(desc_lo), "n"(OFF), "n"(ACC));
}

template <int V> struct IC { static constexpr int value = V; };
template <int J, int E, class F> __device__ __forceinline__ void static_for(F f) {
    if constexpr (J < E) { f(IC<J>{}); static_for<J + 1, E>(f); }
}

__device__ __forceinline__ void make_lut(uint32_t s2, uint32_t z2, uint32_t (&l)[4]) {
    const __nv_bfloat162 s = *reinterpret_cast<__nv_bfloat162*>(&s2), z = *reinterpret_cast<__nv_bfloat162*>(&z2);
    const uint32_t c01 = 0x3F800000u, c23 = 0x40404000u;
    const __nv_bfloat162 q01 = *reinterpret_cast<const __nv_bfloat162*>(&c01), q23 = *reinterpret_cast<const __nv_bfloat162*>(&c23);
    __nv_bfloat162 r0 = __hmul2_rn(__hsub2_rn(q01, __low2bfloat162(z)), __low2bfloat162(s));
    __nv_bfloat162 r1 = __hmul2_rn(__hsub2_rn(q23, __low2bfloat162(z)), __low2bfloat162(s));
    __nv_bfloat162 r2 = __hmul2_rn(__hsub2_rn(q01, __high2bfloat162(z)), __high2bfloat162(s));
    __nv_bfloat162 r3 = __hmul2_rn(__hsub2_rn(q23, __high2bfloat162(z)), __high2bfloat162(s));
    l[0] = *reinterpret_cast<uint32_t*>(&r0); l[1] = *reinterpret_cast<uint32_t*>(&r1);
    l[2] = *reinterpret_cast<uint32_t*>(&r2); l[3] = *reinterpret_cast<uint32_t*>(&r3);
}
__device__ __forceinline__ uint32_t fields(uint32_t w, uint32_t sh) { return prmt(w >> sh, 0, 0x2200) & 0x0C030C03u; }
__device__ __forceinline__ void selectors(uint32_t m, uint32_t coef, uint32_t bias, uint32_t& s0, uint32_t& s1) {
    asm("dp2a.lo.u32.u32 %0, %1, %2, %3;" : "=r"(s0) : "r"(coef), "r"(m), "r"(bias));
    asm("dp2a.hi.u32.u32 %0, %1, %2, %3;" : "=r"(s1) : "r"(coef), "r"(m), "r"(bias));
}
__device__ __forceinline__ uint32_t bitsel(uint32_t m, uint32_t a, uint32_t b) { return (a & m) | (b & ~m); }
__device__ __forceinline__ void regroup(uint32_t wa, uint32_t wb, uint32_t wc, uint32_t wd, uint32_t (&o)[4]) {
    const uint32_t e_ac = bitsel(0x33333333u, wa, wc << 2), o_ac = bitsel(0x33333333u, wa >> 2, wc);
    const uint32_t e_bd = bitsel(0x33333333u, wb, wd << 2), o_bd = bitsel(0x33333333u, wb >> 2, wd);
    const uint32_t a0 = bitsel(0x0F0F0F0Fu, e_ac, o_bd << 4), a1 = bitsel(0x0F0F0F0Fu, e_ac >> 4, o_bd);
    const uint32_t b0 = bitsel(0x0F0F0F0Fu, e_bd, o_ac << 4), b1 = bitsel(0x0F0F0F0Fu, e_bd >> 4, o_ac);
    o[0] = prmt(a0, b0, 0x6240); o[1] = prmt(a1, b1, 0x6240);
    o[2] = prmt(a0, b0, 0x7351); o[3] = prmt(a1, b1, 0x7351);
}

__global__ void __launch_bounds__(NWG * 128 + 128, 1)
gptq_kernel(const uint8_t* __restrict__ xg, const uint8_t* __restrict__ qw, const uint8_t* __restrict__ sc, const uint8_t* __restrict__ ze,
            const __grid_constant__ CUtensorMap tm_x, const __grid_constant__ CUtensorMap tm_o, const __grid_constant__ CUtensorMap tm_w,
            const __grid_constant__ CUtensorMap tm_x2) {
    extern __shared__ __align__(1024) uint8_t smem_raw[];
    const uint32_t sbase = (uint32_t)__cvta_generic_to_shared(smem_raw);
    const int tid = threadIdx.x;
    const int lane = tid & 31;
    const int g = lane >> 2, t = lane & 3;
    const bool extra = blockIdx.x >= 128;
    const int tt = blockIdx.x >> 3, fs = blockIdx.x & 7;
    const int rbase = extra ? (int)(blockIdx.x - 128) * 512 + 96 : tt * BT, rstep = extra ? 128 : 32;
    auto unit_id = [&](int u, int w) {
        const int k = 3 * u + (u == 2 ? (w == WG96 ? 2 : w == 2 ? WG96 : w) : w);
        return extra ? min(k, 7) * 9 + 8 : fs * 9 + k;
    };
    const uint32_t xbar = sbase + SM_BAR;

    if (tid >= NWG * 128) {
        asm volatile("setmaxnreg.dec.sync.aligned.u32 32;");
        const bool lead = elect_one();
        const int w = __shfl_sync(0xffffffffu, (tid >> 5) & 3, 0);
        const uint32_t full = sbase + SM_FULL + w * 16, empty = sbase + SM_EMPTY + w * 8, staged = sbase + SM_STAGED + w * 8;
        const uint32_t slots = sbase + SM_W + 2 * w * WSLOT;
        auto load_x = [&](int j) {
            mbar_expect_tx(xbar + 8 * j, XBLK);
            tma_load_3d(sbase + SM_X + j * XBLK, extra ? &tm_x2 : &tm_x, j * 64, rbase & 127, rbase >> 7, xbar + 8 * j);
        };
        auto load_raw = [&](int n) {
            mbar_expect_tx(full + (n & 1) * 8, WRAW);
            tma_load_2d(slots + (n & 1) * WSLOT, &tm_w, unit_id(0, w) * 64, n * 12, full + (n & 1) * 8);
        };
        if (lead) {
            if (w < NWG) {
                mbar_init(full, 1);
                mbar_init_fence();
                load_raw(0);
                mbar_init(full + 8, 1);
                mbar_init(empty, 4);
                mbar_init(staged, 4);
                mbar_init(xbar + 8 * (w + 6), 1);
                sts32(sbase + SM_CONST + w * 8, 0x1010u);
                sts32(sbase + SM_CONST + w * 8 + 4, w == 0 ? 0x08800022u : w == 1 ? 0x02200022u : 0x00220220u);
            } else {
                mbar_init(xbar + 8, 1);
                mbar_init_fence();
                load_x(1);
                mbar_init(xbar, 256);
                sts32(sbase + SM_CONST + 24, 0x3F800000u);
#pragma unroll
                for (int j = 2; j < 6; j++) mbar_init(xbar + 8 * j, 1);
            }
            mbar_init_fence();
        }
        __syncthreads();
        if (lead) {
            if (w < NWG) load_raw(1);
            else { load_x(2); load_x(3); }
        }
        __syncwarp();
        uint32_t* ready = g_ready + (extra ? lane & 7 : fs) * 32;
        uint32_t epoch = 0;
        if (w == NWG) asm volatile("ld.relaxed.gpu.global.u32 %0, [%1];" : "=r"(epoch) : "l"(ready) : "memory");
        const int item = (tt & 15) * 108 + min(tid - NWG * 128, 107);
        const int prow = item >> 5, pair = item & 31;
        const int uu = prow / 9 + 3, pj = prow % 9;
        const uint32_t pcol = fs * 576 + uu * 64 + pair * 2;
        uint32_t q[4][2];
#pragma unroll
        for (int i = 0; i < 4; i++) ldg64(qw + (uint32_t)(((4 * pj + i) * F_N + pcol) * 4), q[i][0], q[i][1]);
        const uint32_t s2 = ldg32(sc + (uint32_t)((pj * F_N + pcol) * 2));
        const uint32_t z2 = ldg32(ze + (uint32_t)((pj * F_N + pcol) * 2));
        if (w == NWG) {
            mbar_wait(xbar, 0);
            if (lead) {
#pragma unroll
                for (int j = 4; j < NGRP; j++) load_x(j);
                asm volatile("prefetch.tensormap [%0];" ::"l"(&tm_o) : "memory");
            }
            __syncwarp();
        }
        if (!extra) {
            uint32_t o0[4], o1[4], l[4];
            uint8_t* dst = g_prep + ((fs * 9 + uu) * 3 + pj / 3) * WSLOT;
            regroup(q[0][0], q[1][0], q[2][0], q[3][0], o0);
            regroup(q[0][1], q[1][1], q[2][1], q[3][1], o1);
            make_lut(s2, z2, l);
            stg128(dst + (pj % 3) * 1024 + pair * 16, o0[0], o1[0], o0[1], o1[1]);
            stg128(dst + (pj % 3) * 1024 + 512 + (pair ^ 4) * 16, o0[2], o1[2], o0[3], o1[3]);
            stg128(dst + WRAW + (pj % 3) * 512 + pair * 16, l[0], l[1], l[2], l[3]);
        }
        bar_sync(10, 128);
        if (w == NWG) {
            if (extra ? lane < 8 : lead) {
                asm volatile("red.release.gpu.global.add.u32 [%0], %1;" ::"l"(ready), "r"(extra ? 4u : 1u) : "memory");
                const uint32_t target = (epoch & ~31u) + 32u;
                uint32_t seen, spins = 0;
                do {
                    asm volatile("ld.acquire.gpu.global.u32 %0, [%1];" : "=r"(seen) : "l"(ready) : "memory");
                    if (++spins > 0x400000u) __trap();
                } while ((int32_t)(seen - target) < 0);
            }
            __syncwarp();
        } else {
            mbar_wait(empty, 0);
            if (lead) load_raw(2);
            __syncwarp();
        }
        bar_sync(10, 128);
        if (w < NWG && lead) {
            asm volatile("fence.proxy.async.global;" ::: "memory");
#pragma unroll 1
            for (int n = 1; n < 8; n++) {
                mbar_wait(empty, n & 1);
                if (n % 3 == 1) bulk_wait_read();
                if (n < 7) {
                    mbar_expect_tx(full + (n & 1) * 8, WSLOT);
                    bulk_load(slots + (n & 1) * WSLOT, g_prep + (unit_id((n + 2) / 3, w) * 3 + (n + 2) % 3) * WSLOT, WSLOT, full + (n & 1) * 8);
                } else {
                    mbar_arrive(full + (n & 1) * 8);
                }
                if (n % 3 == 0) {
                    mbar_wait(staged, (n / 3 - 1) & 1);
#pragma unroll
                    for (int p = 0; p < 4; p++)
                        tma_store_2d(&tm_o, unit_id(n / 3 - 1, w) * 64, rbase + p * rstep, sbase + SM_O + w * 16384 + 4096 * p);
                    bulk_commit();
                }
            }
        }
        return;
    }

    const int lrow = min(lane >> 3, 2);
    const int colt = unit_id(0, tid >> 7) * 64 + ((tid >> 5) & 3) * 16;
    const uint8_t* ssrc = sc + (uint32_t)(2 * (lrow * F_N + colt + (lane & 7) * 2));
    const uint8_t* zsrc = ze + (uint32_t)(2 * (lrow * F_N + colt + (lane & 7) * 2));
    uint32_t W0[4][2], s_in[3], z_in[3];
#pragma unroll
    for (int i = 0; i < 4; i++) ldg64(qw + (uint32_t)((colt + 2 * g) * 4) + i * F_N * 4, W0[i][0], W0[i][1]);
    s_in[0] = ldg32(ssrc);
    z_in[0] = ldg32(zsrc);
    if (tid < 256) {
        const uint8_t* xsrc = xg + (uint32_t)((rbase + (tid >> 3)) * (D_K * 2) + (tid & 7) * 16);
        const uint32_t xdst = sbase + SM_X + (tid >> 3) * 128 + (((tid & 7) ^ ((tid >> 3) & 7)) << 4);
#pragma unroll
        for (int i = 0; i < 4; i++) cp16(xdst + i * 4096, xsrc + (uint32_t)(i * rstep * (D_K * 2)));
    }
    const int wid = __shfl_sync(0xffffffffu, tid >> 5, 0);
    const int wg = wid >> 2, warp = wid & 3;
    asm volatile("setmaxnreg.inc.sync.aligned.u32 160;");
    __syncthreads();
    if (tid < 256) asm volatile("cp.async.mbarrier.arrive.noinc.shared::cta.b64 [%0];" ::"r"(xbar) : "memory");

    uint32_t coef, bias, coefA, biasA, coefB, biasB;
    lds64(sbase + SM_CONST, bias, coef);
    const uint32_t sh = 4 * t;
    const uint32_t desc0 = (((sbase + SM_X) & 0x3FFFFu) >> 4) | (1u << 16);
    const uint32_t obuf = sbase + SM_O + wg * 16384;
    const uint32_t st_addr0 = obuf + (2 * t) * 128 + (((2 * warp + (g >> 2)) ^ (2 * t)) << 4) + (g & 3) * 4;
    const uint32_t st_addr1 = obuf + (2 * t + 1) * 128 + (((2 * warp + (g >> 2)) ^ (2 * t + 1)) << 4) + (g & 3) * 4;
    const uint32_t slots = sbase + SM_W + wg * 2 * WSLOT;
    const uint32_t full = sbase + SM_FULL + wg * 16, empty = sbase + SM_EMPTY + wg * 8, staged = sbase + SM_STAGED + wg * 8;
    const uint32_t l_ld = slots + WRAW + warp * 128 + g * 16;
    const uint32_t p_ld = slots + (t >> 1) * 512 + ((warp * 8 + g) ^ ((t >> 1) << 2)) * 16 + (t & 1) * 8;

    float acc[64];
    uint32_t A[2][4][4], S[4][4], P[32], lut[4];
    auto lookup = [&](const uint32_t (&sel)[4][4], uint32_t (&dst)[4][4]) {
#pragma unroll
        for (int i = 0; i < 4; i++)
#pragma unroll
            for (int r = 0; r < 4; r++) dst[i][r] = prmt(lut[2 - 2 * (r & 1)], lut[3 - 2 * (r & 1)], sel[i][r]);
    };
    auto mma_group = [&](auto nc, auto jc, const uint32_t (&a)[4][4]) {
        constexpr int j = decltype(jc)::value;
        wg_fence();
        static_for<0, 4>([&](auto ic) {
            constexpr int i = decltype(ic)::value;
            if constexpr (decltype(nc)::value == 128) wgmma_n128<j * (XBLK >> 4) + 2 * i, (j + i > 0)>(acc, a[i], desc0);
            else wgmma_n96<j * (XBLK >> 4) + 2 * i, (j + i > 0)>(acc, a[i], desc0);
        });
        wg_commit();
    };
    auto next_third = [&](int n) {
        mbar_wait(full + 8 * ((n + 1) & 1), ((n + 1) >> 1) & 1);
        if (elect_one()) mbar_arrive(empty);
        __syncwarp();
    };
    auto pack_unit = [&]() {
#pragma unroll
        for (int i = 0; i < 16; i++) {
            P[2 * i] = pack_bf16(acc[4 * i + 2], acc[4 * i + 0]);
            P[2 * i + 1] = pack_bf16(acc[4 * i + 3], acc[4 * i + 1]);
        }
    };
    auto raw_selectors = [&](const uint32_t (&W)[4][2], uint32_t (&sel)[4][4]) {
#pragma unroll
        for (int i = 0; i < 4; i++) {
            selectors(fields(W[i][1], sh), coef, bias, sel[i][0], sel[i][2]);
            selectors(fields(W[i][0], sh), coef, bias, sel[i][1], sel[i][3]);
        }
    };
    auto prep_selectors = [&](uint32_t w0, uint32_t w1, uint32_t (&sel)[4][4]) {
#pragma unroll
        for (int r = 0; r < 2; r++) {
            const uint32_t w = r ? w0 : w1, v = w >> 2;
            selectors(w & 0x30033003u, coefA, biasA, sel[0][r], sel[0][r + 2]);
            selectors(v & 0x30033003u, coefA, biasA, sel[2][r], sel[2][r + 2]);
            selectors(w & 0x03300330u, coefB, biasA, sel[1][r], sel[1][r + 2]);
            selectors(v & 0x03300330u, coefB, biasA, sel[3][r], sel[3][r + 2]);
        }
    };

    {
        const uint32_t w_ld = slots + warp * 64 + g * 8;
        const uint32_t l_st = slots + WRAW + lrow * 512 + warp * 128 + (lane & 7) * 16;
        auto build_table = [&](int r) {
            uint32_t l[4];
            make_lut(s_in[r], z_in[r], l);
            sts128(l_st + (r & 1) * WSLOT, l);
            __syncwarp();
        };
        build_table(0);
        lds128(l_ld, lut);
        raw_selectors(W0, S);
        lookup(S, A[0]);
        if (wg > 0) bar_sync(7 + wg, 256);
        static_for<0, NGRP>([&](auto jc) {
            constexpr int j = decltype(jc)::value;
            mbar_wait(xbar + 8 * j, 0);
            if (j == 0) proxy_fence_shared();
            mma_group(IC<128>{}, jc, A[j % 2]);
            if (j == 0) {
                if (wg < 2) bar_arrive(8 + wg, 256);
#pragma unroll
                for (int r = 1; r < 3; r++) { s_in[r] = ldg32(ssrc + 3 * r * F_N * 2); z_in[r] = ldg32(zsrc + 3 * r * F_N * 2); }
                mbar_wait(full, 0);
            }
            if (j == 2) { build_table(1); build_table(2); }
            if (j % 3 == 2) next_third(j / 3);
            if (j + 1 < NGRP) {
                uint32_t W[4][2], T[4][4];
                const int so = (((j + 1) / 3) & 1) * WSLOT;
#pragma unroll
                for (int i = 0; i < 4; i++) lds64(w_ld + so + (((j + 1) % 3) * 4 + i) * 256, W[i][0], W[i][1]);
                wg_wait<1>();
                __syncwarp();
                lds128(l_ld + so + ((j + 1) % 3) * 512, lut);
                raw_selectors(W, T);
                lookup(T, A[(j + 1) % 2]);
            }
        });
        uint32_t w0, w1;
        lds64(sbase + SM_CONST + 8, biasA, coefA);
        lds64(sbase + SM_CONST + 16, biasB, coefB);
        lds128(l_ld + WSLOT, lut);
        lds64(p_ld + WSLOT, w0, w1);
        prep_selectors(w0, w1, S);
        wg_wait<0>();
        pack_unit();
    }

    auto group = [&](auto nc, auto uc, auto jc) {
        constexpr int u = decltype(uc)::value, j = decltype(jc)::value;
        if (j == 0) lookup(S, A[0]);
        if (u == 1 && j == 3 && wg == 2) bar_sync(11, 256);
        if (u == 1 && j == 1 && wg == 1) bar_sync(12, 256);
        mma_group(nc, jc, A[j % 2]);
        if (u == 1 && j == 8 && wg == 0) bar_arrive(11, 256);
        if (u == 1 && j == 3 && wg == 0) bar_arrive(12, 256);
        if (j == 3) {
            proxy_fence_shared();
            __syncwarp();
            if (elect_one()) mbar_arrive(staged);
            __syncwarp();
        }
        if (j % 3 == 2) next_third(3 * u + j / 3);
        uint32_t w0, w1;
        constexpr int so = ((3 * u + (j + 1) / 3) & 1) * WSLOT;
        if (j + 1 == NGRP) lds128(l_ld + so, lut);
        lds64(p_ld + so + ((j + 1) % 3) * 1024, w0, w1);
        if (j < 3) {
#pragma unroll
            for (int i = (j == 0 ? 0 : j == 1 ? 6 : 11); i < (j == 0 ? 6 : j == 1 ? 11 : 16); i++) {
                sts32(st_addr0 + i * 1024, P[2 * i]);
                sts32(st_addr1 + i * 1024, P[2 * i + 1]);
            }
        }
        if (j + 1 < NGRP) {
            uint32_t T[4][4];
            wg_wait<1>();
            __syncwarp();
            lds128(l_ld + so + ((j + 1) % 3) * 512, lut);
            prep_selectors(w0, w1, T);
            lookup(T, A[(j + 1) % 2]);
        } else {
            prep_selectors(w0, w1, S);
            wg_wait<0>();
            pack_unit();
        }
    };
    auto store_rows = [&](auto q0c, auto q1c, const float* d, int issuer, bool keep) {
        constexpr int q0 = decltype(q0c)::value, q1 = decltype(q1c)::value;
#pragma unroll
        for (int i = 0; i < 4 * (q1 - q0); i++) {
            sts32(st_addr0 + (4 * q0 + i) * 1024, pack_bf16(d[4 * i + 2], d[4 * i + 0]));
            sts32(st_addr1 + (4 * q0 + i) * 1024, pack_bf16(d[4 * i + 3], d[4 * i + 1]));
        }
        proxy_fence_shared();
        bar_sync(1 + wg, 128);
        if (warp == issuer && keep) {
            if (elect_one()) {
#pragma unroll
                for (int q = q0; q < q1; q++) tma_store_2d(&tm_o, unit_id(2, wg) * 64, rbase + q * rstep, obuf + 4096 * q);
                bulk_commit();
            }
            __syncwarp();
        }
    };

    static_for<0, 9>([&](auto jc) { group(IC<128>{}, IC<1>{}, jc); });
    if (wg == WG96) {
        static_for<0, 8>([&](auto jc) { group(IC<96>{}, IC<2>{}, jc); });
        mma_group(IC<96>{}, IC<8>{}, A[0]);
        mbar_wait(full + 8, 0);
        wg_wait<0>();
        store_rows(IC<0>{}, IC<2>{}, acc, 0, !extra);
        store_rows(IC<2>{}, IC<3>{}, acc + 32, 1, !extra);
    } else {
        static_for<0, 7>([&](auto jc) { group(IC<128>{}, IC<2>{}, jc); });
        uint32_t w0, w1;
        lds64(p_ld + 2 * 1024, w0, w1);
        prep_selectors(w0, w1, S);
        mbar_wait(full + 8, 0);
        wg_wait<0>();
        float lo[32], hi[32];
#pragma unroll
        for (int i = 0; i < 32; i++) lo[i] = acc[i];
        auto part = [&](float (&d)[32], auto hc, auto jc) {
            static_for<0, 4>([&](auto ic) {
                constexpr int i = decltype(ic)::value, j = decltype(jc)::value;
                wgmma_n64<j * (XBLK >> 4) + 2 * i + decltype(hc)::value * 512, 1>(d, A[j % 2][i], desc0);
            });
        };
        wg_fence();
        part(lo, IC<0>{}, IC<7>{});
        wg_commit();
        __syncwarp();
        lds128(l_ld + 2 * 512, lut);
        lookup(S, A[0]);
        wg_fence();
        part(lo, IC<0>{}, IC<8>{});
        wg_commit();
        __syncwarp();
        lds64(sbase + SM_CONST + 24, w0, w1);
#pragma unroll
        for (int i = 0; i < 32; i++) hi[i] = acc[32 + i] * __uint_as_float(w0);
        wg_fence();
        part(hi, IC<1>{}, IC<7>{});
        part(hi, IC<1>{}, IC<8>{});
        wg_commit();
        wg_wait<1>();
        store_rows(IC<0>{}, IC<2>{}, lo, 0, true);
        wg_wait<0>();
        store_rows(IC<2>{}, IC<4>{}, hi, 1, true);
    }
    bulk_wait_read();
}

__global__ void gptq_fallback(const __nv_bfloat16* __restrict__ x, const uint32_t* __restrict__ qw, const __nv_bfloat16* __restrict__ sc,
                              const __nv_bfloat16* __restrict__ ze, __nv_bfloat16* __restrict__ out) {
    const int f = blockIdx.x * blockDim.x + threadIdx.x, t0 = blockIdx.y * 8;
    float acc[8] = {};
    for (int k = 0; k < D_K; k++) {
        const float q = (float)((qw[(k >> 4) * F_N + f] >> (2 * (k & 15))) & 3u);
        const __nv_bfloat16 d = __float2bfloat16(q - __bfloat162float(ze[(k >> 6) * F_N + f]));
        const float w = __bfloat162float(__float2bfloat16(__bfloat162float(d) * __bfloat162float(sc[(k >> 6) * F_N + f])));
#pragma unroll
        for (int i = 0; i < 8; i++) acc[i] = fmaf(__bfloat162float(x[(t0 + i) * D_K + k]), w, acc[i]);
    }
#pragma unroll
    for (int i = 0; i < 8; i++) out[(size_t)(t0 + i) * F_N + f] = __float2bfloat16(acc[i]);
}

typedef CUresult (*EncodeFn)(CUtensorMap*, CUtensorMapDataType, cuuint32_t, void*, const cuuint64_t*, const cuuint64_t*,
                             const cuuint32_t*, const cuuint32_t*, CUtensorMapInterleave, CUtensorMapSwizzle,
                             CUtensorMapL2promotion, CUtensorMapFloatOOBfill);

}


extern "C" void kernel_launch(void* const* d_in, const int* in_sizes, int n_in, void* d_out, int out_size) {
    static EncodeFn encode = nullptr;
    static int resident = -1;
    if (resident < 0) {
        void* fn = nullptr;
        cudaDriverEntryPointQueryResult qr;
        cudaGetDriverEntryPoint("cuTensorMapEncodeTiled", &fn, cudaEnableDefault, &qr);
        encode = (EncodeFn)fn;
        cudaFuncSetAttribute(gptq_kernel, cudaFuncAttributeMaxDynamicSharedMemorySize, SM_TOTAL);
        int dev = 0, sms = 0, per_sm = 0;
        cudaGetDevice(&dev);
        cudaDeviceGetAttribute(&sms, cudaDevAttrMultiProcessorCount, dev);
        cudaOccupancyMaxActiveBlocksPerMultiprocessor(&per_sm, gptq_kernel, NWG * 128 + 128, SM_TOTAL);
        resident = sms * per_sm;
    }
    if (!encode || resident < GRID) {
        gptq_fallback<<<dim3(F_N / 128, S_TOK / 8), 128, 0, cudaStreamPerThread>>>(
            (const __nv_bfloat16*)d_in[0], (const uint32_t*)d_in[1], (const __nv_bfloat16*)d_in[2], (const __nv_bfloat16*)d_in[3],
            (__nv_bfloat16*)d_out);
        return;
    }
    CUtensorMap tm_x, tm_o, tm_w, tm_x2;
    for (int v = 0; v < 2; v++) {
        cuuint64_t dims[3] = {D_K, BT, S_TOK / BT}, strides[2] = {D_K * 2, D_K * 2 * BT};
        cuuint32_t box[3] = {64, v ? 32u : 128u, v ? 4u : 1u}, es[3] = {1, 1, 1};
        encode(v ? &tm_x2 : &tm_x, CU_TENSOR_MAP_DATA_TYPE_BFLOAT16, 3, d_in[0], dims, strides, box, es, CU_TENSOR_MAP_INTERLEAVE_NONE,
               CU_TENSOR_MAP_SWIZZLE_128B, CU_TENSOR_MAP_L2_PROMOTION_L2_128B, CU_TENSOR_MAP_FLOAT_OOB_FILL_NONE);
    }
    {
        cuuint64_t dims[2] = {F_N, S_TOK}, strides[1] = {F_N * 2};
        cuuint32_t box[2] = {64, 32}, es[2] = {1, 1};
        encode(&tm_o, CU_TENSOR_MAP_DATA_TYPE_BFLOAT16, 2, d_out, dims, strides, box, es, CU_TENSOR_MAP_INTERLEAVE_NONE,
               CU_TENSOR_MAP_SWIZZLE_128B, CU_TENSOR_MAP_L2_PROMOTION_NONE, CU_TENSOR_MAP_FLOAT_OOB_FILL_NONE);
    }
    {
        cuuint64_t dims[2] = {F_N, 36}, strides[1] = {F_N * 4};
        cuuint32_t box[2] = {64, 12}, es[2] = {1, 1};
        encode(&tm_w, CU_TENSOR_MAP_DATA_TYPE_INT32, 2, d_in[1], dims, strides, box, es, CU_TENSOR_MAP_INTERLEAVE_NONE,
               CU_TENSOR_MAP_SWIZZLE_NONE, CU_TENSOR_MAP_L2_PROMOTION_L2_128B, CU_TENSOR_MAP_FLOAT_OOB_FILL_NONE);
    }
    gptq_kernel<<<GRID, NWG * 128 + 128, SM_TOTAL, cudaStreamPerThread>>>(
        (const uint8_t*)d_in[0], (const uint8_t*)d_in[1], (const uint8_t*)d_in[2], (const uint8_t*)d_in[3], tm_x, tm_o, tm_w, tm_x2);
}
```

```cpp
#include <cuda_runtime.h>
#include <cuda_bf16.h>
#include <cuda.h>
#include <stdint.h>

namespace {

constexpr int S_TOK = 2048, D_K = 576, F_N = 4608, NGRP = 9;
constexpr int BT = 128;
constexpr int NWG = 3;
constexpr int GRID = 132;
constexpr int WG96 = 1;
constexpr int XBLK = BT * 128;
constexpr int WRAW = 12 * 256;
constexpr int WSLOT = WRAW + 3 * 512;
constexpr int SM_X = 0;
constexpr int SM_O = NGRP * XBLK;
constexpr int SM_W = SM_O + NWG * 16384;
constexpr int SM_BAR = SM_W + NWG * 2 * WSLOT;
constexpr int SM_FULL = SM_BAR + 80;
constexpr int SM_EMPTY = SM_FULL + NWG * 16;
constexpr int SM_STAGED = SM_EMPTY + NWG * 8;
constexpr int SM_LAST = SM_STAGED + NWG * 8;
constexpr int SM_CONST = SM_LAST + NWG * 8;
constexpr int SM_TOTAL = SM_CONST + 32;

__device__ __align__(128) uint8_t g_prep[72 * 3 * WSLOT];
__device__ uint32_t g_ready[8 * 32];


__device__ __forceinline__ void mbar_init(uint32_t bar, uint32_t cnt) {
    asm volatile("mbarrier.init.shared::cta.b64 [%0], %1;" ::"r"(bar), "r"(cnt));
}
__device__ __forceinline__ void mbar_init_fence() { asm volatile("fence.mbarrier_init.release.cluster;" ::: "memory"); }
__device__ __forceinline__ void mbar_expect_tx(uint32_t bar, uint32_t bytes) {
    asm volatile("mbarrier.arrive.expect_tx.shared::cta.b64 _, [%0], %1;" ::"r"(bar), "r"(bytes) : "memory");
}
__device__ __forceinline__ void mbar_arrive(uint32_t bar) {
    asm volatile("mbarrier.arrive.shared::cta.b64 _, [%0];" ::"r"(bar) : "memory");
}
__device__ __forceinline__ void mbar_wait(uint32_t bar, uint32_t parity) {
    asm volatile("{\n.reg .pred p;\n.reg .u32 c;\n"
                 "mbarrier.try_wait.parity.shared::cta.b64 p, [%0], %1;\n"
                 "@p bra LAB_DONE;\n"
                 "mov.u32 c, 0;\n"
                 "LAB_WAIT:\n"
                 "mbarrier.try_wait.parity.shared::cta.b64 p, [%0], %1;\n"
                 "@p bra LAB_DONE;\n"
                 "add.u32 c, c, 1;\n"
                 "setp.lt.u32 p, c, 0x400000;\n"
                 "@p bra LAB_WAIT;\n"
                 "trap;\n"
                 "LAB_DONE:\n}\n" ::"r"(bar), "r"(parity) : "memory");
}
__device__ __forceinline__ void tma_load_2d(uint32_t dst, const CUtensorMap* m, int c0, int c1, uint32_t bar) {
    asm volatile("cp.async.bulk.tensor.2d.shared::cluster.global.mbarrier::complete_tx::bytes [%0], [%1, {%3, %4}], [%2];"
                 ::"r"(dst), "l"(m), "r"(bar), "r"(c0), "r"(c1) : "memory");
}
__device__ __forceinline__ void tma_load_3d(uint32_t dst, const CUtensorMap* m, int c0, int c1, int c2, uint32_t bar) {
    asm volatile("cp.async.bulk.tensor.3d.shared::cluster.global.mbarrier::complete_tx::bytes [%0], [%1, {%3, %4, %5}], [%2];"
                 ::"r"(dst), "l"(m), "r"(bar), "r"(c0), "r"(c1), "r"(c2) : "memory");
}
__device__ __forceinline__ void tma_store_2d(const CUtensorMap* m, int c0, int c1, uint32_t src) {
    asm volatile("cp.async.bulk.tensor.2d.global.shared::cta.bulk_group [%0, {%2, %3}], [%1];"
                 ::"l"(m), "r"(src), "r"(c0), "r"(c1) : "memory");
}
__device__ __forceinline__ void bulk_load(uint32_t dst, const void* src, uint32_t bytes, uint32_t bar) {
    asm volatile("cp.async.bulk.shared::cluster.global.mbarrier::complete_tx::bytes [%0], [%1], %2, [%3];"
                 ::"r"(dst), "l"(src), "r"(bytes), "r"(bar) : "memory");
}
__device__ __forceinline__ void bulk_commit() { asm volatile("cp.async.bulk.commit_group;" ::: "memory"); }
__device__ __forceinline__ void bulk_wait_read() { asm volatile("cp.async.bulk.wait_group.read 0;" ::: "memory"); }
__device__ __forceinline__ void proxy_fence_shared() { asm volatile("fence.proxy.async.shared::cta;" ::: "memory"); }
__device__ __forceinline__ bool elect_one() {
    uint32_t p;
    asm volatile("{\n.reg .pred q;\nelect.sync _|q, 0xffffffff;\nselp.b32 %0, 1, 0, q;\n}\n" : "=r"(p));
    return p != 0;
}
__device__ __forceinline__ void wg_fence() { asm volatile("wgmma.fence.sync.aligned;" ::: "memory"); }
__device__ __forceinline__ void wg_commit() { asm volatile("wgmma.commit_group.sync.aligned;" ::: "memory"); }
template <int N> __device__ __forceinline__ void wg_wait() { asm volatile("wgmma.wait_group.sync.aligned %0;" ::"n"(N) : "memory"); }
__device__ __forceinline__ void bar_sync(int id, int n) { asm volatile("bar.sync %0, %1;" ::"r"(id), "r"(n) : "memory"); }
__device__ __forceinline__ void bar_arrive(int id, int n) { asm volatile("bar.arrive %0, %1;" ::"r"(id), "r"(n) : "memory"); }
__device__ __forceinline__ uint32_t ldg32(const void* p) {
    uint32_t v;
    asm volatile("ld.global.nc.b32 %0, [%1];" : "=r"(v) : "l"(p));
    return v;
}
__device__ __forceinline__ void ldg64(const void* p, uint32_t& a, uint32_t& b) {
    asm volatile("ld.global.nc.v2.b32 {%0, %1}, [%2];" : "=r"(a), "=r"(b) : "l"(p));
}
__device__ __forceinline__ void stg128(void* p, uint32_t a, uint32_t b, uint32_t c, uint32_t d) {
    asm volatile("st.global.v4.b32 [%0], {%1, %2, %3, %4};" ::"l"(p), "r"(a), "r"(b), "r"(c), "r"(d) : "memory");
}
__device__ __forceinline__ void lds64(uint32_t addr, uint32_t& a, uint32_t& b) {
    asm volatile("ld.shared.v2.b32 {%0, %1}, [%2];" : "=r"(a), "=r"(b) : "r"(addr) : "memory");
}
__device__ __forceinline__ void lds128(uint32_t addr, uint32_t (&v)[4]) {
    asm volatile("ld.shared.v4.b32 {%0, %1, %2, %3}, [%4];" : "=r"(v[0]), "=r"(v[1]), "=r"(v[2]), "=r"(v[3]) : "r"(addr) : "memory");
}
__device__ __forceinline__ void sts32(uint32_t addr, uint32_t v) { asm volatile("st.shared.b32 [%0], %1;" ::"r"(addr), "r"(v) : "memory"); }
__device__ __forceinline__ void sts128(uint32_t addr, const uint32_t (&v)[4]) {
    asm volatile("st.shared.v4.b32 [%0], {%1, %2, %3, %4};" ::"r"(addr), "r"(v[0]), "r"(v[1]), "r"(v[2]), "r"(v[3]) : "memory");
}
__device__ __forceinline__ void cp16(uint32_t dst, const void* src) {
    asm volatile("cp.async.cg.shared.global [%0], [%1], 16;" ::"r"(dst), "l"(src) : "memory");
}
__device__ __forceinline__ uint32_t prmt(uint32_t a, uint32_t b, uint32_t c) {
    uint32_t d;
    asm("prmt.b32 %0, %1, %2, %3;" : "=r"(d) : "r"(a), "r"(b), "r"(c));
    return d;
}
__device__ __forceinline__ uint32_t pack_bf16(float lo, float hi) {
    uint32_t d;
    asm("cvt.rn.bf16x2.f32 %0, %1, %2;" : "=r"(d) : "f"(hi), "f"(lo));
    return d;
}

template <int OFF, int ACC, int ND>
__device__ __forceinline__ void wgmma_n128(float (&d)[ND], const uint32_t (&a)[4], uint32_t desc_lo) {
    asm volatile("{\n.reg .pred p;\n.reg .b32 lo;\n.reg .b64 db;\n"
        "setp.ne.b32 p, %70, 0;\nadd.u32 lo, %68, %69;\nmov.b64 db, {lo, 0x40000040};\n"
        "wgmma.mma_async.sync.aligned.m64n128k16.f32.bf16.bf16 "
        "{%0, %1, %2, %3, %4, %5, %6, %7, %8, %9, %10, %11, %12, %13, %14, %15, "
        "%16, %17, %18, %19, %20, %21, %22, %23, %24, %25, %26, %27, %28, %29, %30, %31, "
        "%32, %33, %34, %35, %36, %37, %38, %39, %40, %41, %42, %43, %44, %45, %46, %47, "
        "%48, %49, %50, %51, %52, %53, %54, %55, %56, %57, %58, %59, %60, %61, %62, %63}, "
        "{%64, %65, %66, %67}, db, p, 1, 1, 0;\n}\n"
        : "+f"(d[0]), "+f"(d[1]), "+f"(d[2]), "+f"(d[3]), "+f"(d[4]), "+f"(d[5]), "+f"(d[6]), "+f"(d[7]),
          "+f"(d[8]), "+f"(d[9]), "+f"(d[10]), "+f"(d[11]), "+f"(d[12]), "+f"(d[13]), "+f"(d[14]), "+f"(d[15]),
          "+f"(d[16]), "+f"(d[17]), "+f"(d[18]), "+f"(d[19]), "+f"(d[20]), "+f"(d[21]), "+f"(d[22]), "+f"(d[23]),
          "+f"(d[24]), "+f"(d[25]), "+f"(d[26]), "+f"(d[27]), "+f"(d[28]), "+f"(d[29]), "+f"(d[30]), "+f"(d[31]),
          "+f"(d[32]), "+f"(d[33]), "+f"(d[34]), "+f"(d[35]), "+f"(d[36]), "+f"(d[37]), "+f"(d[38]), "+f"(d[39]),
          "+f"(d[40]), "+f"(d[41]), "+f"(d[42]), "+f"(d[43]), "+f"(d[44]), "+f"(d[45]), "+f"(d[46]), "+f"(d[47]),
          "+f"(d[48]), "+f"(d[49]), "+f"(d[50]), "+f"(d[51]), "+f"(d[52]), "+f"(d[53]), "+f"(d[54]), "+f"(d[55]),
          "+f"(d[56]), "+f"(d[57]), "+f"(d[58]), "+f"(d[59]), "+f"(d[60]), "+f"(d[61]), "+f"(d[62]), "+f"(d[63])
        : "r"(a[0]), "r"(a[1]), "r"(a[2]), "r"(a[3]), "r"(desc_lo), "n"(OFF), "n"(ACC));
}
template <int OFF, int ACC, int ND>
__device__ __forceinline__ void wgmma_n96(float (&d)[ND], const uint32_t (&a)[4], uint32_t desc_lo) {
    asm volatile("{\n.reg .pred p;\n.reg .b32 lo;\n.reg .b64 db;\n"
        "setp.ne.b32 p, %54, 0;\nadd.u32 lo, %52, %53;\nmov.b64 db, {lo, 0x40000040};\n"
        "wgmma.mma_async.sync.aligned.m64n96k16.f32.bf16.bf16 "
        "{%0, %1, %2, %3, %4, %5, %6, %7, %8, %9, %10, %11, %12, %13, %14, %15, "
        "%16, %17, %18, %19, %20, %21, %22, %23, %24, %25, %26, %27, %28, %29, %30, %31, "
        "%32, %33, %34, %35, %36, %37, %38, %39, %40, %41, %42, %43, %44, %45, %46, %47}, "
        "{%48, %49, %50, %51}, db, p, 1, 1, 0;\n}\n"
        : "+f"(d[0]), "+f"(d[1]), "+f"(d[2]), "+f"(d[3]), "+f"(d[4]), "+f"(d[5]), "+f"(d[6]), "+f"(d[7]),
          "+f"(d[8]), "+f"(d[9]), "+f"(d[10]), "+f"(d[11]), "+f"(d[12]), "+f"(d[13]), "+f"(d[14]), "+f"(d[15]),
          "+f"(d[16]), "+f"(d[17]), "+f"(d[18]), "+f"(d[19]), "+f"(d[20]), "+f"(d[21]), "+f"(d[22]), "+f"(d[23]),
          "+f"(d[24]), "+f"(d[25]), "+f"(d[26]), "+f"(d[27]), "+f"(d[28]), "+f"(d[29]), "+f"(d[30]), "+f"(d[31]),
          "+f"(d[32]), "+f"(d[33]), "+f"(d[34]), "+f"(d[35]), "+f"(d[36]), "+f"(d[37]), "+f"(d[38]), "+f"(d[39]),
          "+f"(d[40]), "+f"(d[41]), "+f"(d[42]), "+f"(d[43]), "+f"(d[44]), "+f"(d[45]), "+f"(d[46]), "+f"(d[47])
        : "r"(a[0]), "r"(a[1]), "r"(a[2]), "r"(a[3]), "r"(desc_lo), "n"(OFF), "n"(ACC));
}
template <int OFF, int ACC, int ND>
__device__ __forceinline__ void wgmma_n64(float (&d)[ND], const uint32_t (&a)[4], uint32_t desc_lo) {
    asm volatile("{\n.reg .pred p;\n.reg .b32 lo;\n.reg .b64 db;\n"
        "setp.ne.b32 p, %38, 0;\nadd.u32 lo, %36, %37;\nmov.b64 db, {lo, 0x40000040};\n"
        "wgmma.mma_async.sync.aligned.m64n64k16.f32.bf16.bf16 "
        "{%0, %1, %2, %3, %4, %5, %6, %7, %8, %9, %10, %11, %12, %13, %14, %15, "
        "%16, %17, %18, %19, %20, %21, %22, %23, %24, %25, %26, %27, %28, %29, %30, %31}, "
        "{%32, %33, %34, %35}, db, p, 1, 1, 0;\n}\n"
        : "+f"(d[0]), "+f"(d[1]), "+f"(d[2]), "+f"(d[3]), "+f"(d[4]), "+f"(d[5]), "+f"(d[6]), "+f"(d[7]),
          "+f"(d[8]), "+f"(d[9]), "+f"(d[10]), "+f"(d[11]), "+f"(d[12]), "+f"(d[13]), "+f"(d[14]), "+f"(d[15]),
          "+f"(d[16]), "+f"(d[17]), "+f"(d[18]), "+f"(d[19]), "+f"(d[20]), "+f"(d[21]), "+f"(d[22]), "+f"(d[23]),
          "+f"(d[24]), "+f"(d[25]), "+f"(d[26]), "+f"(d[27]), "+f"(d[28]), "+f"(d[29]), "+f"(d[30]), "+f"(d[31])
        : "r"(a[0]), "r"(a[1]), "r"(a[2]), "r"(a[3]), "r"(desc_lo), "n"(OFF), "n"(ACC));
}

template <int V> struct IC { static constexpr int value = V; };
template <int J, int E, class F> __device__ __forceinline__ void static_for(F f) {
    if constexpr (J < E) { f(IC<J>{}); static_for<J + 1, E>(f); }
}

__device__ __forceinline__ void make_lut(uint32_t s2, uint32_t z2, uint32_t (&l)[4]) {
    const __nv_bfloat162 s = *reinterpret_cast<__nv_bfloat162*>(&s2), z = *reinterpret_cast<__nv_bfloat162*>(&z2);
    const uint32_t c01 = 0x3F800000u, c23 = 0x40404000u;
    const __nv_bfloat162 q01 = *reinterpret_cast<const __nv_bfloat162*>(&c01), q23 = *reinterpret_cast<const __nv_bfloat162*>(&c23);
    __nv_bfloat162 r0 = __hmul2_rn(__hsub2_rn(q01, __low2bfloat162(z)), __low2bfloat162(s));
    __nv_bfloat162 r1 = __hmul2_rn(__hsub2_rn(q23, __low2bfloat162(z)), __low2bfloat162(s));
    __nv_bfloat162 r2 = __hmul2_rn(__hsub2_rn(q01, __high2bfloat162(z)), __high2bfloat162(s));
    __nv_bfloat162 r3 = __hmul2_rn(__hsub2_rn(q23, __high2bfloat162(z)), __high2bfloat162(s));
    l[0] = *reinterpret_cast<uint32_t*>(&r0); l[1] = *reinterpret_cast<uint32_t*>(&r1);
    l[2] = *reinterpret_cast<uint32_t*>(&r2); l[3] = *reinterpret_cast<uint32_t*>(&r3);
}
__device__ __forceinline__ uint32_t fields(uint32_t w, uint32_t sh) { return prmt(w >> sh, 0, 0x2200) & 0x0C030C03u; }
__device__ __forceinline__ void selectors(uint32_t m, uint32_t coef, uint32_t bias, uint32_t& s0, uint32_t& s1) {
    asm("dp2a.lo.u32.u32 %0, %1, %2, %3;" : "=r"(s0) : "r"(coef), "r"(m), "r"(bias));
    asm("dp2a.hi.u32.u32 %0, %1, %2, %3;" : "=r"(s1) : "r"(coef), "r"(m), "r"(bias));
}
__device__ __forceinline__ uint32_t bitsel(uint32_t m, uint32_t a, uint32_t b) { return (a & m) | (b & ~m); }
__device__ __forceinline__ void regroup(uint32_t wa, uint32_t wb, uint32_t wc, uint32_t wd, uint32_t (&o)[4]) {
    const uint32_t e_ac = bitsel(0x33333333u, wa, wc << 2), o_ac = bitsel(0x33333333u, wa >> 2, wc);
    const uint32_t e_bd = bitsel(0x33333333u, wb, wd << 2), o_bd = bitsel(0x33333333u, wb >> 2, wd);
    const uint32_t a0 = bitsel(0x0F0F0F0Fu, e_ac, o_bd << 4), a1 = bitsel(0x0F0F0F0Fu, e_ac >> 4, o_bd);
    const uint32_t b0 = bitsel(0x0F0F0F0Fu, e_bd, o_ac << 4), b1 = bitsel(0x0F0F0F0Fu, e_bd >> 4, o_ac);
    o[0] = prmt(a0, b0, 0x6240); o[1] = prmt(a1, b1, 0x6240);
    o[2] = prmt(a0, b0, 0x7351); o[3] = prmt(a1, b1, 0x7351);
}

__global__ void __launch_bounds__(NWG * 128 + 128, 1)
gptq_kernel(const uint8_t* __restrict__ xg, const uint8_t* __restrict__ qw, const uint8_t* __restrict__ sc, const uint8_t* __restrict__ ze,
            const __grid_constant__ CUtensorMap tm_x, const __grid_constant__ CUtensorMap tm_o, const __grid_constant__ CUtensorMap tm_w,
            const __grid_constant__ CUtensorMap tm_x2) {
    extern __shared__ __align__(1024) uint8_t smem_raw[];
    const uint32_t sbase = (uint32_t)__cvta_generic_to_shared(smem_raw);
    const int tid = threadIdx.x;
    const int lane = tid & 31;
    const int g = lane >> 2, t = lane & 3;
    const bool extra = blockIdx.x >= 128;
    const int tt = blockIdx.x >> 3, fs = blockIdx.x & 7;
    const int rbase = extra ? (int)(blockIdx.x - 128) * 512 + 96 : tt * BT, rstep = extra ? 128 : 32;
    auto unit_id = [&](int u, int w) {
        const int k = 3 * u + (u == 2 ? (w == WG96 ? 2 : w == 2 ? WG96 : w) : w);
        return extra ? min(k, 7) * 9 + 8 : fs * 9 + k;
    };
    const uint32_t xbar = sbase + SM_BAR;

    if (tid >= NWG * 128) {
        asm volatile("setmaxnreg.dec.sync.aligned.u32 32;");
        const bool lead = elect_one();
        const int w = __shfl_sync(0xffffffffu, (tid >> 5) & 3, 0);
        const uint32_t full = sbase + SM_FULL + w * 16, empty = sbase + SM_EMPTY + w * 8, staged = sbase + SM_STAGED + w * 8;
        const uint32_t slots = sbase + SM_W + 2 * w * WSLOT;
        auto load_x = [&](int j) {
            mbar_expect_tx(xbar + 8 * j, XBLK);
            tma_load_3d(sbase + SM_X + j * XBLK, extra ? &tm_x2 : &tm_x, j * 64, rbase & 127, rbase >> 7, xbar + 8 * j);
        };
        auto load_raw = [&](int n) {
            mbar_expect_tx(full + (n & 1) * 8, WRAW);
            tma_load_2d(slots + (n & 1) * WSLOT, &tm_w, unit_id(0, w) * 64, n * 12, full + (n & 1) * 8);
        };
        if (lead) {
            if (w < NWG) {
                mbar_init(full, 1);
                mbar_init_fence();
                load_raw(0);
                mbar_init(full + 8, 1);
                mbar_init(empty, 4);
                mbar_init(staged, 4);
                mbar_init(sbase + SM_LAST + w * 8, 4);
                mbar_init(xbar + 8 * (w + 6), 1);
                sts32(sbase + SM_CONST + w * 8, 0x1010u);
                sts32(sbase + SM_CONST + w * 8 + 4, w == 0 ? 0x08800022u : w == 1 ? 0x02200022u : 0x00220220u);
            } else {
                mbar_init(xbar + 8, 1);
                mbar_init_fence();
                load_x(1);
                mbar_init(xbar, 256);
                sts32(sbase + SM_CONST + 24, 0x3F800000u);
#pragma unroll
                for (int j = 2; j < 6; j++) mbar_init(xbar + 8 * j, 1);
            }
            mbar_init_fence();
        }
        __syncthreads();
        if (lead) {
            if (w < NWG) load_raw(1);
            else { load_x(2); load_x(3); }
        }
        __syncwarp();
        uint32_t* ready = g_ready + (extra ? lane & 7 : fs) * 32;
        uint32_t epoch = 0;
        if (w == NWG) asm volatile("ld.relaxed.gpu.global.u32 %0, [%1];" : "=r"(epoch) : "l"(ready) : "memory");
        const int item = (tt & 15) * 108 + min(tid - NWG * 128, 107);
        const int prow = item >> 5, pair = item & 31;
        const int uu = prow / 9 + 3, pj = prow % 9;
        const uint32_t pcol = fs * 576 + uu * 64 + pair * 2;
        uint32_t q[4][2];
#pragma unroll
        for (int i = 0; i < 4; i++) ldg64(qw + (uint32_t)(((4 * pj + i) * F_N + pcol) * 4), q[i][0], q[i][1]);
        const uint32_t s2 = ldg32(sc + (uint32_t)((pj * F_N + pcol) * 2));
        const uint32_t z2 = ldg32(ze + (uint32_t)((pj * F_N + pcol) * 2));
        if (w == NWG) {
            mbar_wait(xbar, 0);
            if (lead) {
#pragma unroll
                for (int j = 4; j < NGRP; j++) load_x(j);
                asm volatile("prefetch.tensormap [%0];" ::"l"(&tm_o) : "memory");
            }
            __syncwarp();
        }
        if (!extra) {
            uint32_t o0[4], o1[4], l[4];
            uint8_t* dst = g_prep + ((fs * 9 + uu) * 3 + pj / 3) * WSLOT;
            regroup(q[0][0], q[1][0], q[2][0], q[3][0], o0);
            regroup(q[0][1], q[1][1], q[2][1], q[3][1], o1);
            make_lut(s2, z2, l);
            stg128(dst + (pj % 3) * 1024 + pair * 16, o0[0], o1[0], o0[1], o1[1]);
            stg128(dst + (pj % 3) * 1024 + 512 + (pair ^ 4) * 16, o0[2], o1[2], o0[3], o1[3]);
            stg128(dst + WRAW + (pj % 3) * 512 + pair * 16, l[0], l[1], l[2], l[3]);
        }
        bar_sync(10, 128);
        if (w == NWG) {
            if (extra ? lane < 8 : lead) {
                asm volatile("red.release.gpu.global.add.u32 [%0], %1;" ::"l"(ready), "r"(extra ? 4u : 1u) : "memory");
                const uint32_t target = (epoch & ~31u) + 32u;
                uint32_t seen, spins = 0;
                do {
                    asm volatile("ld.acquire.gpu.global.u32 %0, [%1];" : "=r"(seen) : "l"(ready) : "memory");
                    if (++spins > 0x400000u) __trap();
                } while ((int32_t)(seen - target) < 0);
            }
            __syncwarp();
        } else {
            mbar_wait(empty, 0);
            if (lead) load_raw(2);
            __syncwarp();
        }
        bar_sync(10, 128);
        if (w < NWG && lead) {
            asm volatile("fence.proxy.async.global;" ::: "memory");
#pragma unroll 1
            for (int n = 1; n < 8; n++) {
                mbar_wait(empty, n & 1);
                if (n % 3 == 1) bulk_wait_read();
                if (n < 7) {
                    mbar_expect_tx(full + (n & 1) * 8, WSLOT);
                    bulk_load(slots + (n & 1) * WSLOT, g_prep + (unit_id((n + 2) / 3, w) * 3 + (n + 2) % 3) * WSLOT, WSLOT, full + (n & 1) * 8);
                } else {
                    mbar_arrive(full + (n & 1) * 8);
                }
                if (n % 3 == 0) {
                    mbar_wait(staged, (n / 3 - 1) & 1);
#pragma unroll
                    for (int p = 0; p < 4; p++)
                        tma_store_2d(&tm_o, unit_id(n / 3 - 1, w) * 64, rbase + p * rstep, sbase + SM_O + w * 16384 + 4096 * p);
                    bulk_commit();
                }
            }
            if (w != WG96 || !extra) {
                const int col = unit_id(2, w) * 64;
                mbar_wait(staged, 0);
                tma_store_2d(&tm_o, col, rbase, sbase + SM_O + w * 16384);
                tma_store_2d(&tm_o, col, rbase + rstep, sbase + SM_O + w * 16384 + 4096);
                mbar_wait(sbase + SM_LAST + w * 8, 0);
                tma_store_2d(&tm_o, col, rbase + 2 * rstep, sbase + SM_O + w * 16384 + 8192);
                if (w != WG96) tma_store_2d(&tm_o, col, rbase + 3 * rstep, sbase + SM_O + w * 16384 + 12288);
                bulk_commit();
                bulk_wait_read();
            }
        }
        return;
    }

    const int lrow = min(lane >> 3, 2);
    const int colt = unit_id(0, tid >> 7) * 64 + ((tid >> 5) & 3) * 16;
    const uint8_t* ssrc = sc + (uint32_t)(2 * (lrow * F_N + colt + (lane & 7) * 2));
    const uint8_t* zsrc = ze + (uint32_t)(2 * (lrow * F_N + colt + (lane & 7) * 2));
    uint32_t W0[4][2], s_in[3], z_in[3];
#pragma unroll
    for (int i = 0; i < 4; i++) ldg64(qw + (uint32_t)((colt + 2 * g) * 4) + i * F_N * 4, W0[i][0], W0[i][1]);
    s_in[0] = ldg32(ssrc);
    z_in[0] = ldg32(zsrc);
    if (tid < 256) {
        const uint8_t* xsrc = xg + (uint32_t)((rbase + (tid >> 3)) * (D_K * 2) + (tid & 7) * 16);
        const uint32_t xdst = sbase + SM_X + (tid >> 3) * 128 + (((tid & 7) ^ ((tid >> 3) & 7)) << 4);
#pragma unroll
        for (int i = 0; i < 4; i++) cp16(xdst + i * 4096, xsrc + (uint32_t)(i * rstep * (D_K * 2)));
    }
    const int wid = __shfl_sync(0xffffffffu, tid >> 5, 0);
    const int wg = wid >> 2, warp = wid & 3;
    asm volatile("setmaxnreg.inc.sync.aligned.u32 160;");
    __syncthreads();
    if (tid < 256) asm volatile("cp.async.mbarrier.arrive.noinc.shared::cta.b64 [%0];" ::"r"(xbar) : "memory");

    uint32_t coef, bias, coefA, biasA, coefB, biasB;
    lds64(sbase + SM_CONST, bias, coef);
    const uint32_t sh = 4 * t;
    const uint32_t desc0 = (((sbase + SM_X) & 0x3FFFFu) >> 4) | (1u << 16);
    const uint32_t obuf = sbase + SM_O + wg * 16384;
    const uint32_t st_addr0 = obuf + (2 * t) * 128 + (((2 * warp + (g >> 2)) ^ (2 * t)) << 4) + (g & 3) * 4;
    const uint32_t st_addr1 = obuf + (2 * t + 1) * 128 + (((2 * warp + (g >> 2)) ^ (2 * t + 1)) << 4) + (g & 3) * 4;
    const uint32_t slots = sbase + SM_W + wg * 2 * WSLOT;
    const uint32_t full = sbase + SM_FULL + wg * 16, empty = sbase + SM_EMPTY + wg * 8, staged = sbase + SM_STAGED + wg * 8;
    const uint32_t l_ld = slots + WRAW + warp * 128 + g * 16;
    const uint32_t p_ld = slots + (t >> 1) * 512 + ((warp * 8 + g) ^ ((t >> 1) << 2)) * 16 + (t & 1) * 8;

    float acc[64];
    uint32_t A[2][4][4], S[4][4], P[32], lut[4];
    auto lookup = [&](const uint32_t (&sel)[4][4], uint32_t (&dst)[4][4]) {
#pragma unroll
        for (int i = 0; i < 4; i++)
#pragma unroll
            for (int r = 0; r < 4; r++) dst[i][r] = prmt(lut[2 - 2 * (r & 1)], lut[3 - 2 * (r & 1)], sel[i][r]);
    };
    auto mma_group = [&](auto nc, auto jc, const uint32_t (&a)[4][4]) {
        constexpr int j = decltype(jc)::value;
        wg_fence();
        static_for<0, 4>([&](auto ic) {
            constexpr int i = decltype(ic)::value;
            if constexpr (decltype(nc)::value == 128) wgmma_n128<j * (XBLK >> 4) + 2 * i, (j + i > 0)>(acc, a[i], desc0);
            else wgmma_n96<j * (XBLK >> 4) + 2 * i, (j + i > 0)>(acc, a[i], desc0);
        });
        wg_commit();
    };
    auto next_third = [&](int n) {
        mbar_wait(full + 8 * ((n + 1) & 1), ((n + 1) >> 1) & 1);
        if (elect_one()) mbar_arrive(empty);
        __syncwarp();
    };
    auto pack_unit = [&]() {
#pragma unroll
        for (int i = 0; i < 16; i++) {
            P[2 * i] = pack_bf16(acc[4 * i + 2], acc[4 * i + 0]);
            P[2 * i + 1] = pack_bf16(acc[4 * i + 3], acc[4 * i + 1]);
        }
    };
    auto raw_selectors = [&](const uint32_t (&W)[4][2], uint32_t (&sel)[4][4]) {
#pragma unroll
        for (int i = 0; i < 4; i++) {
            selectors(fields(W[i][1], sh), coef, bias, sel[i][0], sel[i][2]);
            selectors(fields(W[i][0], sh), coef, bias, sel[i][1], sel[i][3]);
        }
    };
    auto prep_selectors = [&](uint32_t w0, uint32_t w1, uint32_t (&sel)[4][4]) {
#pragma unroll
        for (int r = 0; r < 2; r++) {
            const uint32_t w = r ? w0 : w1, v = w >> 2;
            selectors(w & 0x30033003u, coefA, biasA, sel[0][r], sel[0][r + 2]);
            selectors(v & 0x30033003u, coefA, biasA, sel[2][r], sel[2][r + 2]);
            selectors(w & 0x03300330u, coefB, biasA, sel[1][r], sel[1][r + 2]);
            selectors(v & 0x03300330u, coefB, biasA, sel[3][r], sel[3][r + 2]);
        }
    };

    {
        const uint32_t w_ld = slots + warp * 64 + g * 8;
        const uint32_t l_st = slots + WRAW + lrow * 512 + warp * 128 + (lane & 7) * 16;
        auto build_table = [&](int r) {
            uint32_t l[4];
            make_lut(s_in[r], z_in[r], l);
            sts128(l_st + (r & 1) * WSLOT, l);
            __syncwarp();
        };
        build_table(0);
        lds128(l_ld, lut);
        raw_selectors(W0, S);
        lookup(S, A[0]);
        if (wg > 0) bar_sync(7 + wg, 256);
        static_for<0, NGRP>([&](auto jc) {
            constexpr int j = decltype(jc)::value;
            mbar_wait(xbar + 8 * j, 0);
            if (j == 0) proxy_fence_shared();
            mma_group(IC<128>{}, jc, A[j % 2]);
            if (j == 0) {
                if (wg < 2) bar_arrive(8 + wg, 256);
#pragma unroll
                for (int r = 1; r < 3; r++) { s_in[r] = ldg32(ssrc + 3 * r * F_N * 2); z_in[r] = ldg32(zsrc + 3 * r * F_N * 2); }
                mbar_wait(full, 0);
            }
            if (j == 2) { build_table(1); build_table(2); }
            if (j % 3 == 2) next_third(j / 3);
            if (j + 1 < NGRP) {
                uint32_t W[4][2], T[4][4];
                const int so = (((j + 1) / 3) & 1) * WSLOT;
#pragma unroll
                for (int i = 0; i < 4; i++) lds64(w_ld + so + (((j + 1) % 3) * 4 + i) * 256, W[i][0], W[i][1]);
                wg_wait<1>();
                __syncwarp();
                lds128(l_ld + so + ((j + 1) % 3) * 512, lut);
                raw_selectors(W, T);
                lookup(T, A[(j + 1) % 2]);
            }
        });
        uint32_t w0, w1;
        lds64(sbase + SM_CONST + 8, biasA, coefA);
        lds64(sbase + SM_CONST + 16, biasB, coefB);
        lds128(l_ld + WSLOT, lut);
        lds64(p_ld + WSLOT, w0, w1);
        prep_selectors(w0, w1, S);
        wg_wait<0>();
        pack_unit();
    }

    auto group = [&](auto nc, auto uc, auto jc) {
        constexpr int u = decltype(uc)::value, j = decltype(jc)::value;
        if (j == 0) lookup(S, A[0]);
        if (u == 1 && j == 3 && wg == 2) bar_sync(11, 256);
        if (u == 1 && j == 1 && wg == 1) bar_sync(12, 256);
        mma_group(nc, jc, A[j % 2]);
        if (u == 1 && j == 8 && wg == 0) bar_arrive(11, 256);
        if (u == 1 && j == 3 && wg == 0) bar_arrive(12, 256);
        if (j == 3) {
            proxy_fence_shared();
            __syncwarp();
            if (elect_one()) mbar_arrive(staged);
            __syncwarp();
        }
        if (j % 3 == 2) next_third(3 * u + j / 3);
        uint32_t w0, w1;
        constexpr int so = ((3 * u + (j + 1) / 3) & 1) * WSLOT;
        if (j + 1 == NGRP) lds128(l_ld + so, lut);
        lds64(p_ld + so + ((j + 1) % 3) * 1024, w0, w1);
        if (j < 3) {
#pragma unroll
            for (int i = (j == 0 ? 0 : j == 1 ? 6 : 11); i < (j == 0 ? 6 : j == 1 ? 11 : 16); i++) {
                sts32(st_addr0 + i * 1024, P[2 * i]);
                sts32(st_addr1 + i * 1024, P[2 * i + 1]);
            }
        }
        if (j + 1 < NGRP) {
            uint32_t T[4][4];
            wg_wait<1>();
            __syncwarp();
            lds128(l_ld + so + ((j + 1) % 3) * 512, lut);
            prep_selectors(w0, w1, T);
            lookup(T, A[(j + 1) % 2]);
        } else {
            prep_selectors(w0, w1, S);
            wg_wait<0>();
            pack_unit();
        }
    };
    auto stage_rows = [&](auto q0c, auto q1c, const float* d) {
        constexpr int q0 = decltype(q0c)::value, q1 = decltype(q1c)::value;
#pragma unroll
        for (int i = 0; i < 4 * (q1 - q0); i++) {
            sts32(st_addr0 + (4 * q0 + i) * 1024, pack_bf16(d[4 * i + 2], d[4 * i + 0]));
            sts32(st_addr1 + (4 * q0 + i) * 1024, pack_bf16(d[4 * i + 3], d[4 * i + 1]));
        }
        proxy_fence_shared();
        __syncwarp();
        if (elect_one()) mbar_arrive(q0 == 0 ? staged : sbase + SM_LAST + wg * 8);
        __syncwarp();
    };

    static_for<0, 9>([&](auto jc) { group(IC<128>{}, IC<1>{}, jc); });
    if (wg == WG96) {
        static_for<0, 8>([&](auto jc) { group(IC<96>{}, IC<2>{}, jc); });
        mma_group(IC<96>{}, IC<8>{}, A[0]);
        mbar_wait(full + 8, 0);
        wg_wait<0>();
        stage_rows(IC<0>{}, IC<2>{}, acc);
        stage_rows(IC<2>{}, IC<3>{}, acc + 32);
    } else {
        static_for<0, 7>([&](auto jc) { group(IC<128>{}, IC<2>{}, jc); });
        uint32_t w0, w1;
        lds64(p_ld + 2 * 1024, w0, w1);
        prep_selectors(w0, w1, S);
        mbar_wait(full + 8, 0);
        wg_wait<0>();
        float lo[32], hi[32];
#pragma unroll
        for (int i = 0; i < 32; i++) lo[i] = acc[i];
        auto part = [&](float (&d)[32], auto hc, auto jc) {
            static_for<0, 4>([&](auto ic) {
                constexpr int i = decltype(ic)::value, j = decltype(jc)::value;
                wgmma_n64<j * (XBLK >> 4) + 2 * i + decltype(hc)::value * 512, 1>(d, A[j % 2][i], desc0);
            });
        };
        wg_fence();
        part(lo, IC<0>{}, IC<7>{});
        wg_commit();
        __syncwarp();
        lds128(l_ld + 2 * 512, lut);
        lookup(S, A[0]);
        wg_fence();
        part(lo, IC<0>{}, IC<8>{});
        wg_commit();
        __syncwarp();
        lds64(sbase + SM_CONST + 24, w0, w1);
#pragma unroll
        for (int i = 0; i < 32; i++) hi[i] = acc[32 + i] * __uint_as_float(w0);
        wg_fence();
        part(hi, IC<1>{}, IC<7>{});
        part(hi, IC<1>{}, IC<8>{});
        wg_commit();
        wg_wait<1>();
        stage_rows(IC<0>{}, IC<2>{}, lo);
        wg_wait<0>();
        stage_rows(IC<2>{}, IC<4>{}, hi);
    }
}

__global__ void gptq_fallback(const __nv_bfloat16* __restrict__ x, const uint32_t* __restrict__ qw, const __nv_bfloat16* __restrict__ sc,
                              const __nv_bfloat16* __restrict__ ze, __nv_bfloat16* __restrict__ out) {
    const int f = blockIdx.x * blockDim.x + threadIdx.x, t0 = blockIdx.y * 8;
    float acc[8] = {};
    for (int k = 0; k < D_K; k++) {
        const float q = (float)((qw[(k >> 4) * F_N + f] >> (2 * (k & 15))) & 3u);
        const __nv_bfloat16 d = __float2bfloat16(q - __bfloat162float(ze[(k >> 6) * F_N + f]));
        const float w = __bfloat162float(__float2bfloat16(__bfloat162float(d) * __bfloat162float(sc[(k >> 6) * F_N + f])));
#pragma unroll
        for (int i = 0; i < 8; i++) acc[i] = fmaf(__bfloat162float(x[(t0 + i) * D_K + k]), w, acc[i]);
    }
#pragma unroll
    for (int i = 0; i < 8; i++) out[(size_t)(t0 + i) * F_N + f] = __float2bfloat16(acc[i]);
}

typedef CUresult (*EncodeFn)(CUtensorMap*, CUtensorMapDataType, cuuint32_t, void*, const cuuint64_t*, const cuuint64_t*,
                             const cuuint32_t*, const cuuint32_t*, CUtensorMapInterleave, CUtensorMapSwizzle,
                             CUtensorMapL2promotion, CUtensorMapFloatOOBfill);

}


extern "C" void kernel_launch(void* const* d_in, const int* in_sizes, int n_in, void* d_out, int out_size) {
    static EncodeFn encode = nullptr;
    static int resident = -1;
    if (resident < 0) {
        void* fn = nullptr;
        cudaDriverEntryPointQueryResult qr;
        cudaGetDriverEntryPoint("cuTensorMapEncodeTiled", &fn, cudaEnableDefault, &qr);
        encode = (EncodeFn)fn;
        cudaFuncSetAttribute(gptq_kernel, cudaFuncAttributeMaxDynamicSharedMemorySize, SM_TOTAL);
        int dev = 0, sms = 0, per_sm = 0;
        cudaGetDevice(&dev);
        cudaDeviceGetAttribute(&sms, cudaDevAttrMultiProcessorCount, dev);
        cudaOccupancyMaxActiveBlocksPerMultiprocessor(&per_sm, gptq_kernel, NWG * 128 + 128, SM_TOTAL);
        resident = sms * per_sm;
    }
    if (!encode || resident < GRID) {
        gptq_fallback<<<dim3(F_N / 128, S_TOK / 8), 128, 0, cudaStreamPerThread>>>(
            (const __nv_bfloat16*)d_in[0], (const uint32_t*)d_in[1], (const __nv_bfloat16*)d_in[2], (const __nv_bfloat16*)d_in[3],
            (__nv_bfloat16*)d_out);
        return;
    }
    CUtensorMap tm_x, tm_o, tm_w, tm_x2;
    for (int v = 0; v < 2; v++) {
        cuuint64_t dims[3] = {D_K, BT, S_TOK / BT}, strides[2] = {D_K * 2, D_K * 2 * BT};
        cuuint32_t box[3] = {64, v ? 32u : 128u, v ? 4u : 1u}, es[3] = {1, 1, 1};
        encode(v ? &tm_x2 : &tm_x, CU_TENSOR_MAP_DATA_TYPE_BFLOAT16, 3, d_in[0], dims, strides, box, es, CU_TENSOR_MAP_INTERLEAVE_NONE,
               CU_TENSOR_MAP_SWIZZLE_128B, CU_TENSOR_MAP_L2_PROMOTION_L2_128B, CU_TENSOR_MAP_FLOAT_OOB_FILL_NONE);
    }
    {
        cuuint64_t dims[2] = {F_N, S_TOK}, strides[1] = {F_N * 2};
        cuuint32_t box[2] = {64, 32}, es[2] = {1, 1};
        encode(&tm_o, CU_TENSOR_MAP_DATA_TYPE_BFLOAT16, 2, d_out, dims, strides, box, es, CU_TENSOR_MAP_INTERLEAVE_NONE,
               CU_TENSOR_MAP_SWIZZLE_128B, CU_TENSOR_MAP_L2_PROMOTION_NONE, CU_TENSOR_MAP_FLOAT_OOB_FILL_NONE);
    }
    {
        cuuint64_t dims[2] = {F_N, 36}, strides[1] = {F_N * 4};
        cuuint32_t box[2] = {64, 12}, es[2] = {1, 1};
        encode(&tm_w, CU_TENSOR_MAP_DATA_TYPE_INT32, 2, d_in[1], dims, strides, box, es, CU_TENSOR_MAP_INTERLEAVE_NONE,
               CU_TENSOR_MAP_SWIZZLE_NONE, CU_TENSOR_MAP_L2_PROMOTION_L2_128B, CU_TENSOR_MAP_FLOAT_OOB_FILL_NONE);
    }
    gptq_kernel<<<GRID, NWG * 128 + 128, SM_TOTAL, cudaStreamPerThread>>>(
        (const uint8_t*)d_in[0], (const uint8_t*)d_in[1], (const uint8_t*)d_in[2], (const uint8_t*)d_in[3], tm_x, tm_o, tm_w, tm_x2);
}
```

```cpp
#include <cuda_runtime.h>
#include <cuda_bf16.h>
#include <cuda.h>
#include <stdint.h>

namespace {

constexpr int S_TOK = 2048, D_K = 576, F_N = 4608, NGRP = 9;
constexpr int BT = 128;
constexpr int NWG = 3;
constexpr int GRID = 132;
constexpr int WG96 = 1;
constexpr int XBLK = BT * 128;
constexpr int WRAW = 12 * 256;
constexpr int WSLOT = WRAW + 3 * 512;
constexpr int SM_X = 0;
constexpr int SM_O = NGRP * XBLK;
constexpr int SM_W = SM_O + NWG * 16384;
constexpr int SM_BAR = SM_W + NWG * 2 * WSLOT;
constexpr int SM_FULL = SM_BAR + 80;
constexpr int SM_EMPTY = SM_FULL + NWG * 16;
constexpr int SM_STAGED = SM_EMPTY + NWG * 8;
constexpr int SM_CONST = SM_STAGED + NWG * 8;
constexpr int SM_TOTAL = SM_CONST + 32;

__device__ __align__(128) uint8_t g_prep[72 * 3 * WSLOT];
__device__ uint32_t g_ready[8 * 32];


__device__ __forceinline__ void mbar_init(uint32_t bar, uint32_t cnt) {
    asm volatile("mbarrier.init.shared::cta.b64 [%0], %1;" ::"r"(bar), "r"(cnt));
}
__device__ __forceinline__ void mbar_init_fence() { asm volatile("fence.mbarrier_init.release.cluster;" ::: "memory"); }
__device__ __forceinline__ void mbar_expect_tx(uint32_t bar, uint32_t bytes) {
    asm volatile("mbarrier.arrive.expect_tx.shared::cta.b64 _, [%0], %1;" ::"r"(bar), "r"(bytes) : "memory");
}
__device__ __forceinline__ void mbar_arrive(uint32_t bar) {
    asm volatile("mbarrier.arrive.shared::cta.b64 _, [%0];" ::"r"(bar) : "memory");
}
__device__ __forceinline__ void mbar_wait(uint32_t bar, uint32_t parity) {
    asm volatile("{\n.reg .pred p;\n.reg .u32 c;\n"
                 "mbarrier.try_wait.parity.shared::cta.b64 p, [%0], %1;\n"
                 "@p bra LAB_DONE;\n"
                 "mov.u32 c, 0;\n"
                 "LAB_WAIT:\n"
                 "mbarrier.try_wait.parity.shared::cta.b64 p, [%0], %1;\n"
                 "@p bra LAB_DONE;\n"
                 "add.u32 c, c, 1;\n"
                 "setp.lt.u32 p, c, 0x400000;\n"
                 "@p bra LAB_WAIT;\n"
                 "trap;\n"
                 "LAB_DONE:\n}\n" ::"r"(bar), "r"(parity) : "memory");
}
__device__ __forceinline__ void tma_load_2d(uint32_t dst, const CUtensorMap* m, int c0, int c1, uint32_t bar) {
    asm volatile("cp.async.bulk.tensor.2d.shared::cluster.global.mbarrier::complete_tx::bytes [%0], [%1, {%3, %4}], [%2];"
                 ::"r"(dst), "l"(m), "r"(bar), "r"(c0), "r"(c1) : "memory");
}
__device__ __forceinline__ void tma_load_3d(uint32_t dst, const CUtensorMap* m, int c0, int c1, int c2, uint32_t bar) {
    asm volatile("cp.async.bulk.tensor.3d.shared::cluster.global.mbarrier::complete_tx::bytes [%0], [%1, {%3, %4, %5}], [%2];"
                 ::"r"(dst), "l"(m), "r"(bar), "r"(c0), "r"(c1), "r"(c2) : "memory");
}
__device__ __forceinline__ void tma_store_2d(const CUtensorMap* m, int c0, int c1, uint32_t src) {
    asm volatile("cp.async.bulk.tensor.2d.global.shared::cta.bulk_group [%0, {%2, %3}], [%1];"
                 ::"l"(m), "r"(src), "r"(c0), "r"(c1) : "memory");
}
__device__ __forceinline__ void bulk_load(uint32_t dst, const void* src, uint32_t bytes, uint32_t bar) {
    asm volatile("cp.async.bulk.shared::cluster.global.mbarrier::complete_tx::bytes [%0], [%1], %2, [%3];"
                 ::"r"(dst), "l"(src), "r"(bytes), "r"(bar) : "memory");
}
__device__ __forceinline__ void bulk_commit() { asm volatile("cp.async.bulk.commit_group;" ::: "memory"); }
__device__ __forceinline__ void bulk_wait_read() { asm volatile("cp.async.bulk.wait_group.read 0;" ::: "memory"); }
__device__ __forceinline__ void proxy_fence_shared() { asm volatile("fence.proxy.async.shared::cta;" ::: "memory"); }
__device__ __forceinline__ bool elect_one() {
    uint32_t p;
    asm volatile("{\n.reg .pred q;\nelect.sync _|q, 0xffffffff;\nselp.b32 %0, 1, 0, q;\n}\n" : "=r"(p));
    return p != 0;
}
__device__ __forceinline__ void wg_fence() { asm volatile("wgmma.fence.sync.aligned;" ::: "memory"); }
__device__ __forceinline__ void wg_commit() { asm volatile("wgmma.commit_group.sync.aligned;" ::: "memory"); }
template <int N> __device__ __forceinline__ void wg_wait() { asm volatile("wgmma.wait_group.sync.aligned %0;" ::"n"(N) : "memory"); }
__device__ __forceinline__ void bar_sync(int id, int n) { asm volatile("bar.sync %0, %1;" ::"r"(id), "r"(n) : "memory"); }
__device__ __forceinline__ void bar_arrive(int id, int n) { asm volatile("bar.arrive %0, %1;" ::"r"(id), "r"(n) : "memory"); }
__device__ __forceinline__ uint32_t ldg32(const void* p) {
    uint32_t v;
    asm volatile("ld.global.nc.b32 %0, [%1];" : "=r"(v) : "l"(p));
    return v;
}
__device__ __forceinline__ void ldg64(const void* p, uint32_t& a, uint32_t& b) {
    asm volatile("ld.global.nc.v2.b32 {%0, %1}, [%2];" : "=r"(a), "=r"(b) : "l"(p));
}
__device__ __forceinline__ void stg128(void* p, uint32_t a, uint32_t b, uint32_t c, uint32_t d) {
    asm volatile("st.global.v4.b32 [%0], {%1, %2, %3, %4};" ::"l"(p), "r"(a), "r"(b), "r"(c), "r"(d) : "memory");
}
__device__ __forceinline__ void lds64(uint32_t addr, uint32_t& a, uint32_t& b) {
    asm volatile("ld.shared.v2.b32 {%0, %1}, [%2];" : "=r"(a), "=r"(b) : "r"(addr) : "memory");
}
__device__ __forceinline__ void lds128(uint32_t addr, uint32_t (&v)[4]) {
    asm volatile("ld.shared.v4.b32 {%0, %1, %2, %3}, [%4];" : "=r"(v[0]), "=r"(v[1]), "=r"(v[2]), "=r"(v[3]) : "r"(addr) : "memory");
}
__device__ __forceinline__ void sts32(uint32_t addr, uint32_t v) { asm volatile("st.shared.b32 [%0], %1;" ::"r"(addr), "r"(v) : "memory"); }
__device__ __forceinline__ void sts128(uint32_t addr, const uint32_t (&v)[4]) {
    asm volatile("st.shared.v4.b32 [%0], {%1, %2, %3, %4};" ::"r"(addr), "r"(v[0]), "r"(v[1]), "r"(v[2]), "r"(v[3]) : "memory");
}
__device__ __forceinline__ void cp16(uint32_t dst, const void* src) {
    asm volatile("cp.async.cg.shared.global [%0], [%1], 16;" ::"r"(dst), "l"(src) : "memory");
}
__device__ __forceinline__ uint32_t prmt(uint32_t a, uint32_t b, uint32_t c) {
    uint32_t d;
    asm("prmt.b32 %0, %1, %2, %3;" : "=r"(d) : "r"(a), "r"(b), "r"(c));
    return d;
}
__device__ __forceinline__ uint32_t pack_bf16(float lo, float hi) {
    uint32_t d;
    asm("cvt.rn.bf16x2.f32 %0, %1, %2;" : "=r"(d) : "f"(hi), "f"(lo));
    return d;
}

template <int OFF, int ACC, int ND>
__device__ __forceinline__ void wgmma_n128(float (&d)[ND], const uint32_t (&a)[4], uint32_t desc_lo) {
    asm volatile("{\n.reg .pred p;\n.reg .b32 lo;\n.reg .b64 db;\n"
        "setp.ne.b32 p, %70, 0;\nadd.u32 lo, %68, %69;\nmov.b64 db, {lo, 0x40000040};\n"
        "wgmma.mma_async.sync.aligned.m64n128k16.f32.bf16.bf16 "
        "{%0, %1, %2, %3, %4, %5, %6, %7, %8, %9, %10, %11, %12, %13, %14, %15, "
        "%16, %17, %18, %19, %20, %21, %22, %23, %24, %25, %26, %27, %28, %29, %30, %31, "
        "%32, %33, %34, %35, %36, %37, %38, %39, %40, %41, %42, %43, %44, %45, %46, %47, "
        "%48, %49, %50, %51, %52, %53, %54, %55, %56, %57, %58, %59, %60, %61, %62, %63}, "
        "{%64, %65, %66, %67}, db, p, 1, 1, 0;\n}\n"
        : "+f"(d[0]), "+f"(d[1]), "+f"(d[2]), "+f"(d[3]), "+f"(d[4]), "+f"(d[5]), "+f"(d[6]), "+f"(d[7]),
          "+f"(d[8]), "+f"(d[9]), "+f"(d[10]), "+f"(d[11]), "+f"(d[12]), "+f"(d[13]), "+f"(d[14]), "+f"(d[15]),
          "+f"(d[16]), "+f"(d[17]), "+f"(d[18]), "+f"(d[19]), "+f"(d[20]), "+f"(d[21]), "+f"(d[22]), "+f"(d[23]),
          "+f"(d[24]), "+f"(d[25]), "+f"(d[26]), "+f"(d[27]), "+f"(d[28]), "+f"(d[29]), "+f"(d[30]), "+f"(d[31]),
          "+f"(d[32]), "+f"(d[33]), "+f"(d[34]), "+f"(d[35]), "+f"(d[36]), "+f"(d[37]), "+f"(d[38]), "+f"(d[39]),
          "+f"(d[40]), "+f"(d[41]), "+f"(d[42]), "+f"(d[43]), "+f"(d[44]), "+f"(d[45]), "+f"(d[46]), "+f"(d[47]),
          "+f"(d[48]), "+f"(d[49]), "+f"(d[50]), "+f"(d[51]), "+f"(d[52]), "+f"(d[53]), "+f"(d[54]), "+f"(d[55]),
          "+f"(d[56]), "+f"(d[57]), "+f"(d[58]), "+f"(d[59]), "+f"(d[60]), "+f"(d[61]), "+f"(d[62]), "+f"(d[63])
        : "r"(a[0]), "r"(a[1]), "r"(a[2]), "r"(a[3]), "r"(desc_lo), "n"(OFF), "n"(ACC));
}
template <int OFF, int ACC, int ND>
__device__ __forceinline__ void wgmma_n96(float (&d)[ND], const uint32_t (&a)[4], uint32_t desc_lo) {
    asm volatile("{\n.reg .pred p;\n.reg .b32 lo;\n.reg .b64 db;\n"
        "setp.ne.b32 p, %54, 0;\nadd.u32 lo, %52, %53;\nmov.b64 db, {lo, 0x40000040};\n"
        "wgmma.mma_async.sync.aligned.m64n96k16.f32.bf16.bf16 "
        "{%0, %1, %2, %3, %4, %5, %6, %7, %8, %9, %10, %11, %12, %13, %14, %15, "
        "%16, %17, %18, %19, %20, %21, %22, %23, %24, %25, %26, %27, %28, %29, %30, %31, "
        "%32, %33, %34, %35, %36, %37, %38, %39, %40, %41, %42, %43, %44, %45, %46, %47}, "
        "{%48, %49, %50, %51}, db, p, 1, 1, 0;\n}\n"
        : "+f"(d[0]), "+f"(d[1]), "+f"(d[2]), "+f"(d[3]), "+f"(d[4]), "+f"(d[5]), "+f"(d[6]), "+f"(d[7]),
          "+f"(d[8]), "+f"(d[9]), "+f"(d[10]), "+f"(d[11]), "+f"(d[12]), "+f"(d[13]), "+f"(d[14]), "+f"(d[15]),
          "+f"(d[16]), "+f"(d[17]), "+f"(d[18]), "+f"(d[19]), "+f"(d[20]), "+f"(d[21]), "+f"(d[22]), "+f"(d[23]),
          "+f"(d[24]), "+f"(d[25]), "+f"(d[26]), "+f"(d[27]), "+f"(d[28]), "+f"(d[29]), "+f"(d[30]), "+f"(d[31]),
          "+f"(d[32]), "+f"(d[33]), "+f"(d[34]), "+f"(d[35]), "+f"(d[36]), "+f"(d[37]), "+f"(d[38]), "+f"(d[39]),
          "+f"(d[40]), "+f"(d[41]), "+f"(d[42]), "+f"(d[43]), "+f"(d[44]), "+f"(d[45]), "+f"(d[46]), "+f"(d[47])
        : "r"(a[0]), "r"(a[1]), "r"(a[2]), "r"(a[3]), "r"(desc_lo), "n"(OFF), "n"(ACC));
}
template <int OFF, int ACC, int ND>
__device__ __forceinline__ void wgmma_n64(float (&d)[ND], const uint32_t (&a)[4], uint32_t desc_lo) {
    asm volatile("{\n.reg .pred p;\n.reg .b32 lo;\n.reg .b64 db;\n"
        "setp.ne.b32 p, %38, 0;\nadd.u32 lo, %36, %37;\nmov.b64 db, {lo, 0x40000040};\n"
        "wgmma.mma_async.sync.aligned.m64n64k16.f32.bf16.bf16 "
        "{%0, %1, %2, %3, %4, %5, %6, %7, %8, %9, %10, %11, %12, %13, %14, %15, "
        "%16, %17, %18, %19, %20, %21, %22, %23, %24, %25, %26, %27, %28, %29, %30, %31}, "
        "{%32, %33, %34, %35}, db, p, 1, 1, 0;\n}\n"
        : "+f"(d[0]), "+f"(d[1]), "+f"(d[2]), "+f"(d[3]), "+f"(d[4]), "+f"(d[5]), "+f"(d[6]), "+f"(d[7]),
          "+f"(d[8]), "+f"(d[9]), "+f"(d[10]), "+f"(d[11]), "+f"(d[12]), "+f"(d[13]), "+f"(d[14]), "+f"(d[15]),
          "+f"(d[16]), "+f"(d[17]), "+f"(d[18]), "+f"(d[19]), "+f"(d[20]), "+f"(d[21]), "+f"(d[22]), "+f"(d[23]),
          "+f"(d[24]), "+f"(d[25]), "+f"(d[26]), "+f"(d[27]), "+f"(d[28]), "+f"(d[29]), "+f"(d[30]), "+f"(d[31])
        : "r"(a[0]), "r"(a[1]), "r"(a[2]), "r"(a[3]), "r"(desc_lo), "n"(OFF), "n"(ACC));
}

template <int V> struct IC { static constexpr int value = V; };
template <int J, int E, class F> __device__ __forceinline__ void static_for(F f) {
    if constexpr (J < E) { f(IC<J>{}); static_for<J + 1, E>(f); }
}

__device__ __forceinline__ void make_lut(uint32_t s2, uint32_t z2, uint32_t (&l)[4]) {
    const __nv_bfloat162 s = *reinterpret_cast<__nv_bfloat162*>(&s2), z = *reinterpret_cast<__nv_bfloat162*>(&z2);
    const uint32_t c01 = 0x3F800000u, c23 = 0x40404000u;
    const __nv_bfloat162 q01 = *reinterpret_cast<const __nv_bfloat162*>(&c01), q23 = *reinterpret_cast<const __nv_bfloat162*>(&c23);
    __nv_bfloat162 r0 = __hmul2_rn(__hsub2_rn(q01, __low2bfloat162(z)), __low2bfloat162(s));
    __nv_bfloat162 r1 = __hmul2_rn(__hsub2_rn(q23, __low2bfloat162(z)), __low2bfloat162(s));
    __nv_bfloat162 r2 = __hmul2_rn(__hsub2_rn(q01, __high2bfloat162(z)), __high2bfloat162(s));
    __nv_bfloat162 r3 = __hmul2_rn(__hsub2_rn(q23, __high2bfloat162(z)), __high2bfloat162(s));
    l[0] = *reinterpret_cast<uint32_t*>(&r0); l[1] = *reinterpret_cast<uint32_t*>(&r1);
    l[2] = *reinterpret_cast<uint32_t*>(&r2); l[3] = *reinterpret_cast<uint32_t*>(&r3);
}
__device__ __forceinline__ uint32_t fields(uint32_t w, uint32_t sh) { return prmt(w >> sh, 0, 0x2200) & 0x0C030C03u; }
__device__ __forceinline__ void selectors(uint32_t m, uint32_t coef, uint32_t bias, uint32_t& s0, uint32_t& s1) {
    asm("dp2a.lo.u32.u32 %0, %1, %2, %3;" : "=r"(s0) : "r"(coef), "r"(m), "r"(bias));
    asm("dp2a.hi.u32.u32 %0, %1, %2, %3;" : "=r"(s1) : "r"(coef), "r"(m), "r"(bias));
}
__device__ __forceinline__ uint32_t bitsel(uint32_t m, uint32_t a, uint32_t b) { return (a & m) | (b & ~m); }
__device__ __forceinline__ void regroup(uint32_t wa, uint32_t wb, uint32_t wc, uint32_t wd, uint32_t (&o)[4]) {
    const uint32_t e_ac = bitsel(0x33333333u, wa, wc << 2), o_ac = bitsel(0x33333333u, wa >> 2, wc);
    const uint32_t e_bd = bitsel(0x33333333u, wb, wd << 2), o_bd = bitsel(0x33333333u, wb >> 2, wd);
    const uint32_t a0 = bitsel(0x0F0F0F0Fu, e_ac, o_bd << 4), a1 = bitsel(0x0F0F0F0Fu, e_ac >> 4, o_bd);
    const uint32_t b0 = bitsel(0x0F0F0F0Fu, e_bd, o_ac << 4), b1 = bitsel(0x0F0F0F0Fu, e_bd >> 4, o_ac);
    o[0] = prmt(a0, b0, 0x6240); o[1] = prmt(a1, b1, 0x6240);
    o[2] = prmt(a0, b0, 0x7351); o[3] = prmt(a1, b1, 0x7351);
}

__global__ void __launch_bounds__(NWG * 128 + 128, 1)
gptq_kernel(const uint8_t* __restrict__ xg, const uint8_t* __restrict__ qw, const uint8_t* __restrict__ sc, const uint8_t* __restrict__ ze,
            const __grid_constant__ CUtensorMap tm_x, const __grid_constant__ CUtensorMap tm_o, const __grid_constant__ CUtensorMap tm_w,
            const __grid_constant__ CUtensorMap tm_x2) {
    extern __shared__ __align__(1024) uint8_t smem_raw[];
    const uint32_t sbase = (uint32_t)__cvta_generic_to_shared(smem_raw);
    const int tid = threadIdx.x;
    const int lane = tid & 31;
    const int g = lane >> 2, t = lane & 3;
    const bool extra = blockIdx.x >= 128;
    const int tt = blockIdx.x >> 3, fs = blockIdx.x & 7;
    const int rbase = extra ? (int)(blockIdx.x - 128) * 512 + 96 : tt * BT, rstep = extra ? 128 : 32;
    auto unit_id = [&](int u, int w) {
        const int k = 3 * u + (u == 2 ? (w == WG96 ? 2 : w == 2 ? WG96 : w) : w);
        return extra ? min(k, 7) * 9 + 8 : fs * 9 + k;
    };
    const uint32_t xbar = sbase + SM_BAR;

    if (tid >= NWG * 128) {
        asm volatile("setmaxnreg.dec.sync.aligned.u32 32;");
        const bool lead = elect_one();
        const int w = __shfl_sync(0xffffffffu, (tid >> 5) & 3, 0);
        const uint32_t full = sbase + SM_FULL + w * 16, empty = sbase + SM_EMPTY + w * 8, staged = sbase + SM_STAGED + w * 8;
        const uint32_t slots = sbase + SM_W + 2 * w * WSLOT;
        auto load_x = [&](int j) {
            mbar_expect_tx(xbar + 8 * j, XBLK);
            tma_load_3d(sbase + SM_X + j * XBLK, extra ? &tm_x2 : &tm_x, j * 64, rbase & 127, rbase >> 7, xbar + 8 * j);
        };
        auto load_raw = [&](int n) {
            mbar_expect_tx(full + (n & 1) * 8, WRAW);
            tma_load_2d(slots + (n & 1) * WSLOT, &tm_w, unit_id(0, w) * 64, n * 12, full + (n & 1) * 8);
        };
        if (lead) {
            if (w < NWG) {
                mbar_init(full, 1);
                mbar_init_fence();
                load_raw(0);
                mbar_init(full + 8, 1);
                mbar_init(empty, 4);
                mbar_init(staged, 4);
                mbar_init(xbar + 8 * (w + 6), 1);
                sts32(sbase + SM_CONST + w * 8, 0x1010u);
                sts32(sbase + SM_CONST + w * 8 + 4, w == 0 ? 0x08800022u : w == 1 ? 0x02200022u : 0x00220220u);
            } else {
                mbar_init(xbar + 8, 1);
                mbar_init_fence();
                load_x(1);
                mbar_init(xbar, 256);
                sts32(sbase + SM_CONST + 24, 0x3F800000u);
#pragma unroll
                for (int j = 2; j < 6; j++) mbar_init(xbar + 8 * j, 1);
            }
            mbar_init_fence();
        }
        __syncthreads();
        if (lead) {
            if (w < NWG) load_raw(1);
            else { load_x(2); load_x(3); }
        }
        __syncwarp();
        uint32_t* ready = g_ready + (extra ? lane & 7 : fs) * 32;
        uint32_t epoch = 0;
        if (w == NWG) asm volatile("ld.relaxed.gpu.global.u32 %0, [%1];" : "=r"(epoch) : "l"(ready) : "memory");
        const int item = tt * 108 + min(tid - NWG * 128, 107);
        const int prow = item >> 5, pair = item & 31;
        const int uu = prow / 9 + 3, pj = prow % 9;
        const uint32_t pcol = fs * 576 + uu * 64 + pair * 2;
        uint32_t q[4][2] = {}, s2 = 0, z2 = 0;
        if (!extra) {
#pragma unroll
            for (int i = 0; i < 4; i++) ldg64(qw + (uint32_t)(((4 * pj + i) * F_N + pcol) * 4), q[i][0], q[i][1]);
            s2 = ldg32(sc + (uint32_t)((pj * F_N + pcol) * 2));
            z2 = ldg32(ze + (uint32_t)((pj * F_N + pcol) * 2));
        }
        if (w == NWG) {
            mbar_wait(xbar, 0);
            if (lead) {
#pragma unroll
                for (int j = 4; j < NGRP; j++) load_x(j);
                asm volatile("prefetch.tensormap [%0];" ::"l"(&tm_o) : "memory");
            }
            __syncwarp();
        }
        if (!extra) {
            uint32_t o0[4], o1[4], l[4];
            uint8_t* dst = g_prep + ((fs * 9 + uu) * 3 + pj / 3) * WSLOT;
            regroup(q[0][0], q[1][0], q[2][0], q[3][0], o0);
            regroup(q[0][1], q[1][1], q[2][1], q[3][1], o1);
            make_lut(s2, z2, l);
            stg128(dst + (pj % 3) * 1024 + pair * 16, o0[0], o1[0], o0[1], o1[1]);
            stg128(dst + (pj % 3) * 1024 + 512 + (pair ^ 4) * 16, o0[2], o1[2], o0[3], o1[3]);
            stg128(dst + WRAW + (pj % 3) * 512 + pair * 16, l[0], l[1], l[2], l[3]);
        }
        bar_sync(10, 128);
        if (w == NWG) {
            if (extra ? lane < 8 : lead) {
                asm volatile("red.release.gpu.global.add.u32 [%0], %1;" ::"l"(ready), "r"(extra ? 4u : 1u) : "memory");
                const uint32_t target = (epoch & ~31u) + 32u;
                uint32_t seen, spins = 0;
                do {
                    asm volatile("ld.acquire.gpu.global.u32 %0, [%1];" : "=r"(seen) : "l"(ready) : "memory");
                    if (++spins > 0x400000u) __trap();
                } while ((int32_t)(seen - target) < 0);
            }
            __syncwarp();
        } else {
            mbar_wait(empty, 0);
            if (lead) load_raw(2);
            __syncwarp();
        }
        bar_sync(10, 128);
        if (w < NWG && lead) {
            asm volatile("fence.proxy.async.global;" ::: "memory");
#pragma unroll 1
            for (int n = 1; n < 8; n++) {
                mbar_wait(empty, n & 1);
                if (n % 3 == 1) bulk_wait_read();
                if (n < 7) {
                    mbar_expect_tx(full + (n & 1) * 8, WSLOT);
                    bulk_load(slots + (n & 1) * WSLOT, g_prep + (unit_id((n + 2) / 3, w) * 3 + (n + 2) % 3) * WSLOT, WSLOT, full + (n & 1) * 8);
                } else {
                    mbar_arrive(full + (n & 1) * 8);
                }
                if (n % 3 == 0) {
                    mbar_wait(staged, (n / 3 - 1) & 1);
#pragma unroll
                    for (int p = 0; p < 4; p++)
                        tma_store_2d(&tm_o, unit_id(n / 3 - 1, w) * 64, rbase + p * rstep, sbase + SM_O + w * 16384 + 4096 * p);
                    bulk_commit();
                }
            }
        }
        return;
    }

    const int lrow = min(lane >> 3, 2);
    const int colt = unit_id(0, tid >> 7) * 64 + ((tid >> 5) & 3) * 16;
    const uint8_t* ssrc = sc + (uint32_t)(2 * (lrow * F_N + colt + (lane & 7) * 2));
    const uint8_t* zsrc = ze + (uint32_t)(2 * (lrow * F_N + colt + (lane & 7) * 2));
    uint32_t W0[4][2], s_in[3], z_in[3];
#pragma unroll
    for (int i = 0; i < 4; i++) ldg64(qw + (uint32_t)((colt + 2 * g) * 4) + i * F_N * 4, W0[i][0], W0[i][1]);
    s_in[0] = ldg32(ssrc);
    z_in[0] = ldg32(zsrc);
    if (tid < 256) {
        const uint8_t* xsrc = xg + (uint32_t)((rbase + (tid >> 3)) * (D_K * 2) + (tid & 7) * 16);
        const uint32_t xdst = sbase + SM_X + (tid >> 3) * 128 + (((tid & 7) ^ ((tid >> 3) & 7)) << 4);
#pragma unroll
        for (int i = 0; i < 4; i++) cp16(xdst + i * 4096, xsrc + (uint32_t)(i * rstep * (D_K * 2)));
    }
    const int wid = __shfl_sync(0xffffffffu, tid >> 5, 0);
    const int wg = wid >> 2, warp = wid & 3;
    asm volatile("setmaxnreg.inc.sync.aligned.u32 160;");
    __syncthreads();
    if (tid < 256) asm volatile("cp.async.mbarrier.arrive.noinc.shared::cta.b64 [%0];" ::"r"(xbar) : "memory");

    uint32_t coef, bias, coefA, biasA, coefB, biasB;
    lds64(sbase + SM_CONST, bias, coef);
    const uint32_t sh = 4 * t;
    const uint32_t desc0 = (((sbase + SM_X) & 0x3FFFFu) >> 4) | (1u << 16);
    const uint32_t obuf = sbase + SM_O + wg * 16384;
    const uint32_t st_addr0 = obuf + (2 * t) * 128 + (((2 * warp + (g >> 2)) ^ (2 * t)) << 4) + (g & 3) * 4;
    const uint32_t st_addr1 = obuf + (2 * t + 1) * 128 + (((2 * warp + (g >> 2)) ^ (2 * t + 1)) << 4) + (g & 3) * 4;
    const uint32_t slots = sbase + SM_W + wg * 2 * WSLOT;
    const uint32_t full = sbase + SM_FULL + wg * 16, empty = sbase + SM_EMPTY + wg * 8, staged = sbase + SM_STAGED + wg * 8;
    const uint32_t l_ld = slots + WRAW + warp * 128 + g * 16;
    const uint32_t p_ld = slots + (t >> 1) * 512 + ((warp * 8 + g) ^ ((t >> 1) << 2)) * 16 + (t & 1) * 8;

    float acc[64];
    uint32_t A[2][4][4], S[4][4], P[32], lut[4];
    auto lookup = [&](const uint32_t (&sel)[4][4], uint32_t (&dst)[4][4]) {
#pragma unroll
        for (int i = 0; i < 4; i++)
#pragma unroll
            for (int r = 0; r < 4; r++) dst[i][r] = prmt(lut[2 - 2 * (r & 1)], lut[3 - 2 * (r & 1)], sel[i][r]);
    };
    auto mma_group = [&](auto nc, auto jc, const uint32_t (&a)[4][4]) {
        constexpr int j = decltype(jc)::value;
        wg_fence();
        static_for<0, 4>([&](auto ic) {
            constexpr int i = decltype(ic)::value;
            if constexpr (decltype(nc)::value == 128) wgmma_n128<j * (XBLK >> 4) + 2 * i, (j + i > 0)>(acc, a[i], desc0);
            else wgmma_n96<j * (XBLK >> 4) + 2 * i, (j + i > 0)>(acc, a[i], desc0);
        });
        wg_commit();
    };
    auto next_third = [&](int n) {
        mbar_wait(full + 8 * ((n + 1) & 1), ((n + 1) >> 1) & 1);
        if (elect_one()) mbar_arrive(empty);
        __syncwarp();
    };
    auto pack_unit = [&]() {
#pragma unroll
        for (int i = 0; i < 16; i++) {
            P[2 * i] = pack_bf16(acc[4 * i + 2], acc[4 * i + 0]);
            P[2 * i + 1] = pack_bf16(acc[4 * i + 3], acc[4 * i + 1]);
        }
    };
    auto raw_selectors = [&](const uint32_t (&W)[4][2], uint32_t (&sel)[4][4]) {
#pragma unroll
        for (int i = 0; i < 4; i++) {
            selectors(fields(W[i][1], sh), coef, bias, sel[i][0], sel[i][2]);
            selectors(fields(W[i][0], sh), coef, bias, sel[i][1], sel[i][3]);
        }
    };
    auto prep_selectors = [&](uint32_t w0, uint32_t w1, uint32_t (&sel)[4][4]) {
#pragma unroll
        for (int r = 0; r < 2; r++) {
            const uint32_t w = r ? w0 : w1, v = w >> 2;
            selectors(w & 0x30033003u, coefA, biasA, sel[0][r], sel[0][r + 2]);
            selectors(v & 0x30033003u, coefA, biasA, sel[2][r], sel[2][r + 2]);
            selectors(w & 0x03300330u, coefB, biasA, sel[1][r], sel[1][r + 2]);
            selectors(v & 0x03300330u, coefB, biasA, sel[3][r], sel[3][r + 2]);
        }
    };

    {
        const uint32_t w_ld = slots + warp * 64 + g * 8;
        const uint32_t l_st = slots + WRAW + lrow * 512 + warp * 128 + (lane & 7) * 16;
        auto build_table = [&](int r) {
            uint32_t l[4];
            make_lut(s_in[r], z_in[r], l);
            sts128(l_st + (r & 1) * WSLOT, l);
            __syncwarp();
        };
        build_table(0);
        lds128(l_ld, lut);
        raw_selectors(W0, S);
        lookup(S, A[0]);
        if (wg > 0) bar_sync(7 + wg, 256);
        static_for<0, NGRP>([&](auto jc) {
            constexpr int j = decltype(jc)::value;
            mbar_wait(xbar + 8 * j, 0);
            if (j == 0) proxy_fence_shared();
            mma_group(IC<128>{}, jc, A[j % 2]);
            if (j == 0) {
                if (wg < 2) bar_arrive(8 + wg, 256);
#pragma unroll
                for (int r = 1; r < 3; r++) { s_in[r] = ldg32(ssrc + 3 * r * F_N * 2); z_in[r] = ldg32(zsrc + 3 * r * F_N * 2); }
                mbar_wait(full, 0);
            }
            if (j == 2) { build_table(1); build_table(2); }
            if (j % 3 == 2) next_third(j / 3);
            if (j + 1 < NGRP) {
                uint32_t W[4][2], T[4][4];
                const int so = (((j + 1) / 3) & 1) * WSLOT;
#pragma unroll
                for (int i = 0; i < 4; i++) lds64(w_ld + so + (((j + 1) % 3) * 4 + i) * 256, W[i][0], W[i][1]);
                wg_wait<1>();
                __syncwarp();
                lds128(l_ld + so + ((j + 1) % 3) * 512, lut);
                raw_selectors(W, T);
                lookup(T, A[(j + 1) % 2]);
            }
        });
        uint32_t w0, w1;
        lds64(sbase + SM_CONST + 8, biasA, coefA);
        lds64(sbase + SM_CONST + 16, biasB, coefB);
        lds128(l_ld + WSLOT, lut);
        lds64(p_ld + WSLOT, w0, w1);
        prep_selectors(w0, w1, S);
        wg_wait<0>();
        pack_unit();
    }

    auto group = [&](auto nc, auto uc, auto jc) {
        constexpr int u = decltype(uc)::value, j = decltype(jc)::value;
        if (j == 0) lookup(S, A[0]);
        if (u == 1 && j == 3 && wg == 2) bar_sync(11, 256);
        if (u == 1 && j == 1 && wg == 1) bar_sync(12, 256);
        mma_group(nc, jc, A[j % 2]);
        if (u == 1 && j == 8 && wg == 0) bar_arrive(11, 256);
        if (u == 1 && j == 3 && wg == 0) bar_arrive(12, 256);
        if (j == 3) {
            proxy_fence_shared();
            __syncwarp();
            if (elect_one()) mbar_arrive(staged);
            __syncwarp();
        }
        if (j % 3 == 2) next_third(3 * u + j / 3);
        uint32_t w0, w1;
        constexpr int so = ((3 * u + (j + 1) / 3) & 1) * WSLOT;
        if (j + 1 == NGRP) lds128(l_ld + so, lut);
        lds64(p_ld + so + ((j + 1) % 3) * 1024, w0, w1);
        if (j < 3) {
#pragma unroll
            for (int i = (j == 0 ? 0 : j == 1 ? 6 : 11); i < (j == 0 ? 6 : j == 1 ? 11 : 16); i++) {
                sts32(st_addr0 + i * 1024, P[2 * i]);
                sts32(st_addr1 + i * 1024, P[2 * i + 1]);
            }
        }
        if (j + 1 < NGRP) {
            uint32_t T[4][4];
            wg_wait<1>();
            __syncwarp();
            lds128(l_ld + so + ((j + 1) % 3) * 512, lut);
            prep_selectors(w0, w1, T);
            lookup(T, A[(j + 1) % 2]);
        } else {
            prep_selectors(w0, w1, S);
            wg_wait<0>();
            pack_unit();
        }
    };
    auto store_rows = [&](auto q0c, auto q1c, const float* d, int issuer, bool keep) {
        constexpr int q0 = decltype(q0c)::value, q1 = decltype(q1c)::value;
#pragma unroll
        for (int i = 0; i < 4 * (q1 - q0); i++) {
            sts32(st_addr0 + (4 * q0 + i) * 1024, pack_bf16(d[4 * i + 2], d[4 * i + 0]));
            sts32(st_addr1 + (4 * q0 + i) * 1024, pack_bf16(d[4 * i + 3], d[4 * i + 1]));
        }
        proxy_fence_shared();
        bar_sync(1 + wg, 128);
        if (warp == issuer && keep) {
            if (elect_one()) {
#pragma unroll
                for (int q = q0; q < q1; q++) tma_store_2d(&tm_o, unit_id(2, wg) * 64, rbase + q * rstep, obuf + 4096 * q);
                bulk_commit();
            }
            __syncwarp();
        }
    };

    static_for<0, 9>([&](auto jc) { group(IC<128>{}, IC<1>{}, jc); });
    if (wg == WG96) {
        static_for<0, 8>([&](auto jc) { group(IC<96>{}, IC<2>{}, jc); });
        mma_group(IC<96>{}, IC<8>{}, A[0]);
        mbar_wait(full + 8, 0);
        wg_wait<0>();
        store_rows(IC<0>{}, IC<2>{}, acc, 0, !extra);
        store_rows(IC<2>{}, IC<3>{}, acc + 32, 1, !extra);
    } else {
        static_for<0, 7>([&](auto jc) { group(IC<128>{}, IC<2>{}, jc); });
        uint32_t w0, w1;
        lds64(p_ld + 2 * 1024, w0, w1);
        prep_selectors(w0, w1, S);
        mbar_wait(full + 8, 0);
        wg_wait<0>();
        float lo[32], hi[32];
#pragma unroll
        for (int i = 0; i < 32; i++) lo[i] = acc[i];
        auto part = [&](float (&d)[32], auto hc, auto jc) {
            static_for<0, 4>([&](auto ic) {
                constexpr int i = decltype(ic)::value, j = decltype(jc)::value;
                wgmma_n64<j * (XBLK >> 4) + 2 * i + decltype(hc)::value * 512, 1>(d, A[j % 2][i], desc0);
            });
        };
        wg_fence();
        part(lo, IC<0>{}, IC<7>{});
        wg_commit();
        __syncwarp();
        lds128(l_ld + 2 * 512, lut);
        lookup(S, A[0]);
        wg_fence();
        part(lo, IC<0>{}, IC<8>{});
        wg_commit();
        __syncwarp();
        lds64(sbase + SM_CONST + 24, w0, w1);
#pragma unroll
        for (int i = 0; i < 32; i++) hi[i] = acc[32 + i] * __uint_as_float(w0);
        wg_fence();
        part(hi, IC<1>{}, IC<7>{});
        part(hi, IC<1>{}, IC<8>{});
        wg_commit();
        wg_wait<1>();
        store_rows(IC<0>{}, IC<2>{}, lo, 0, true);
        wg_wait<0>();
        store_rows(IC<2>{}, IC<4>{}, hi, 1, true);
    }
    bulk_wait_read();
}

__global__ void gptq_fallback(const __nv_bfloat16* __restrict__ x, const uint32_t* __restrict__ qw, const __nv_bfloat16* __restrict__ sc,
                              const __nv_bfloat16* __restrict__ ze, __nv_bfloat16* __restrict__ out) {
    const int f = blockIdx.x * blockDim.x + threadIdx.x, t0 = blockIdx.y * 8;
    float acc[8] = {};
    for (int k = 0; k < D_K; k++) {
        const float q = (float)((qw[(k >> 4) * F_N + f] >> (2 * (k & 15))) & 3u);
        const __nv_bfloat16 d = __float2bfloat16(q - __bfloat162float(ze[(k >> 6) * F_N + f]));
        const float w = __bfloat162float(__float2bfloat16(__bfloat162float(d) * __bfloat162float(sc[(k >> 6) * F_N + f])));
#pragma unroll
        for (int i = 0; i < 8; i++) acc[i] = fmaf(__bfloat162float(x[(t0 + i) * D_K + k]), w, acc[i]);
    }
#pragma unroll
    for (int i = 0; i < 8; i++) out[(size_t)(t0 + i) * F_N + f] = __float2bfloat16(acc[i]);
}

typedef CUresult (*EncodeFn)(CUtensorMap*, CUtensorMapDataType, cuuint32_t, void*, const cuuint64_t*, const cuuint64_t*,
                             const cuuint32_t*, const cuuint32_t*, CUtensorMapInterleave, CUtensorMapSwizzle,
                             CUtensorMapL2promotion, CUtensorMapFloatOOBfill);

}


extern "C" void kernel_launch(void* const* d_in, const int* in_sizes, int n_in, void* d_out, int out_size) {
    static EncodeFn encode = nullptr;
    static int resident = -1;
    if (resident < 0) {
        void* fn = nullptr;
        cudaDriverEntryPointQueryResult qr;
        cudaGetDriverEntryPoint("cuTensorMapEncodeTiled", &fn, cudaEnableDefault, &qr);
        encode = (EncodeFn)fn;
        cudaFuncSetAttribute(gptq_kernel, cudaFuncAttributeMaxDynamicSharedMemorySize, SM_TOTAL);
        int dev = 0, sms = 0, per_sm = 0;
        cudaGetDevice(&dev);
        cudaDeviceGetAttribute(&sms, cudaDevAttrMultiProcessorCount, dev);
        cudaOccupancyMaxActiveBlocksPerMultiprocessor(&per_sm, gptq_kernel, NWG * 128 + 128, SM_TOTAL);
        resident = sms * per_sm;
    }
    if (!encode || resident < GRID) {
        gptq_fallback<<<dim3(F_N / 128, S_TOK / 8), 128, 0, cudaStreamPerThread>>>(
            (const __nv_bfloat16*)d_in[0], (const uint32_t*)d_in[1], (const __nv_bfloat16*)d_in[2], (const __nv_bfloat16*)d_in[3],
            (__nv_bfloat16*)d_out);
        return;
    }
    CUtensorMap tm_x, tm_o, tm_w, tm_x2;
    for (int v = 0; v < 2; v++) {
        cuuint64_t dims[3] = {D_K, BT, S_TOK / BT}, strides[2] = {D_K * 2, D_K * 2 * BT};
        cuuint32_t box[3] = {64, v ? 32u : 128u, v ? 4u : 1u}, es[3] = {1, 1, 1};
        encode(v ? &tm_x2 : &tm_x, CU_TENSOR_MAP_DATA_TYPE_BFLOAT16, 3, d_in[0], dims, strides, box, es, CU_TENSOR_MAP_INTERLEAVE_NONE,
               CU_TENSOR_MAP_SWIZZLE_128B, CU_TENSOR_MAP_L2_PROMOTION_L2_128B, CU_TENSOR_MAP_FLOAT_OOB_FILL_NONE);
    }
    {
        cuuint64_t dims[2] = {F_N, S_TOK}, strides[1] = {F_N * 2};
        cuuint32_t box[2] = {64, 32}, es[2] = {1, 1};
        encode(&tm_o, CU_TENSOR_MAP_DATA_TYPE_BFLOAT16, 2, d_out, dims, strides, box, es, CU_TENSOR_MAP_INTERLEAVE_NONE,
               CU_TENSOR_MAP_SWIZZLE_128B, CU_TENSOR_MAP_L2_PROMOTION_NONE, CU_TENSOR_MAP_FLOAT_OOB_FILL_NONE);
    }
    {
        cuuint64_t dims[2] = {F_N, 36}, strides[1] = {F_N * 4};
        cuuint32_t box[2] = {64, 12}, es[2] = {1, 1};
        encode(&tm_w, CU_TENSOR_MAP_DATA_TYPE_INT32, 2, d_in[1], dims, strides, box, es, CU_TENSOR_MAP_INTERLEAVE_NONE,
               CU_TENSOR_MAP_SWIZZLE_NONE, CU_TENSOR_MAP_L2_PROMOTION_L2_128B, CU_TENSOR_MAP_FLOAT_OOB_FILL_NONE);
    }
    gptq_kernel<<<GRID, NWG * 128 + 128, SM_TOTAL, cudaStreamPerThread>>>(
        (const uint8_t*)d_in[0], (const uint8_t*)d_in[1], (const uint8_t*)d_in[2], (const uint8_t*)d_in[3], tm_x, tm_o, tm_w, tm_x2);
}
```
